```python
import torch

def _softmax(x, axis=-1):
    return torch.softmax(x, dim=axis)
def _gelu(x):
    return torch.nn.functional.gelu(x, approximate="tanh")
def _silu(x):
    return torch.nn.functional.silu(x)
def _sigmoid(x):
    return torch.sigmoid(x)
def _layernorm(x, axis=-1, eps=1e-5):
    m = x.mean(dim=axis, keepdim=True)
    v = x.var(dim=axis, keepdim=True, unbiased=False)
    return (x - m) / torch.sqrt(v + eps)
def _scatter_add(tgt, idx, src, axis=0):
    return tgt.clone().index_add_(axis, idx, src)
def _segment_sum(src, seg, n):
    out = torch.zeros((n,) + src.shape[1:], dtype=src.dtype)
    return out.index_add_(0, seg, src)
def _pad(x, pw):
    flat = tuple(v for pair in reversed(pw) for v in pair)
    return torch.nn.functional.pad(x, flat)

kernel_name = 'gated_mix__mha_block_cached__glu_gated_bilinear__decode'

def setup_inputs():

    _w = (lambda a: (lambda t: t.to(torch.bfloat16) if t.is_floating_point() else t)(torch.as_tensor(a)))
    def _A_setup():
        B, Sq, D = 1, 1, 512
        H, Sk, Dh = 32, 8192, 128
        return {
            "x": _w((lambda *s: torch.randn(*s, dtype=torch.bfloat16) * 0.05)(B, Sq, D)),
            "k_cache": _w((lambda *s: torch.randn(*s, dtype=torch.bfloat16) * 3.2)(B, H, Sk, Dh)),
            "v_cache": _w((lambda *s: torch.randn(*s, dtype=torch.bfloat16) * 0.2)(B, H, Sk, Dh)),
            "wq": _w((lambda *s: torch.randn(*s, dtype=torch.bfloat16) * 3.2)(D, H * Dh) * (D ** -0.5)),
            "wo": _w((lambda *s: torch.randn(*s, dtype=torch.bfloat16) * 0.2)(H * Dh, D) * ((H * Dh) ** -0.5)),
        }
    _A_in = _A_setup()

    def _B_setup():
        B, S, D, F = 1, 1, 512, 1376
        return {
            "x": _w((lambda *s: torch.randn(*s, dtype=torch.bfloat16) * 0.05)(B, S, D)),
            "w_gate": _w((lambda *s: torch.randn(*s, dtype=torch.bfloat16) * 0.8)(D, F) * (D ** -0.5)),
            "w_up": _w((lambda *s: torch.randn(*s, dtype=torch.bfloat16) * 0.8)(D, F) * (D ** -0.5)),
            "w_down": _w((lambda *s: torch.randn(*s, dtype=torch.bfloat16) * 0.8)(F, D) * (F ** -0.5)),
        }
    _B_in = _B_setup()

    return {
        "A_x": _A_in["x"],
        "A_k_cache": _A_in["k_cache"],
        "A_v_cache": _A_in["v_cache"],
        "A_wq": _A_in["wq"],
        "A_wo": _A_in["wo"],
        "B_x": _B_in["x"],
        "B_w_gate": _B_in["w_gate"],
        "B_w_up": _B_in["w_up"],
        "B_w_down": _B_in["w_down"],
        "gate_w": _w((lambda *s: torch.randn(*s, dtype=torch.bfloat16) * 0.1)(512) * 16.0),
    }

def reference(A_x, A_k_cache, A_v_cache, A_wq, A_wo, B_x, B_w_gate, B_w_up, B_w_down, gate_w):
    def _A_ref(x, k_cache, v_cache, wq, wo):
        B, Sq, D = x.shape
        H, Dh = 32, 128
        q = (lambda x, *d: x.permute(*d))((x @ wq).reshape(B, Sq, H, Dh), 0, 2, 1, 3)
        scores = torch.einsum("bhqd,bhkd->bhqk", q, k_cache) * (Dh ** -0.5)
        p = _softmax(scores, axis=-1)
        o = torch.einsum("bhqk,bhkd->bhqd", p, v_cache)
        return (lambda x, *d: x.permute(*d))(o, 0, 2, 1, 3).reshape(B, Sq, H * Dh) @ wo

    def _B_ref(x, w_gate, w_up, w_down):
        g = torch.einsum("bsd,df->bsf", x, w_gate)
        u = torch.einsum("bsd,df->bsf", x, w_up)
        h = g * u
        return torch.einsum("bsf,fd->bsd", h, w_down)

    x = A_x
    g = _sigmoid((x * gate_w).sum(-1, keepdims=True))
    a = _A_ref(x, A_k_cache, A_v_cache, A_wq, A_wo)
    b = _B_ref(x, B_w_gate, B_w_up, B_w_down)
    return g * a + (1 - g) * b
```

```cpp
#include <cuda_runtime.h>
#include <cuda_bf16.h>
#include <stdint.h>

namespace {

constexpr int D_MODEL = 512;
constexpr int NH = 32;
constexpr int SK = 8192;
constexpr int DH = 128;
constexpr int FF = 1376;
constexpr int NSPLIT = 4;
constexpr int NCTA = NH * NSPLIT;
constexpr int KEYS_CTA = SK / NSPLIT;
constexpr int NW = 8;
constexpr int WT_BYTES = 32 * DH * 2;
constexpr int TW = 2;
constexpr int TT_BYTES = TW * WT_BYTES;
constexpr int NS = 12;
constexpr int SLOT_BYTES = TT_BYTES + 256;
constexpr int TPW = KEYS_CTA / 32 / NW;
constexpr int NTT = 2 * TPW * NW / TW;
constexpr int NTHREADS = NW * 32 + 64;
#define WIN 4
#define FB 160
#define FLAG_AT 4
#define WARM 1

constexpr int SM_RING = 0;
constexpr int SM_RED = SM_RING + NS * SLOT_BYTES;
constexpr int RED_WSTRIDE = 2096;
constexpr int SM_P = SM_RED + NW * RED_WSTRIDE;
constexpr int SM_Q = SM_P + NW * TPW * 32 * 2;
constexpr int SM_O = SM_Q + 256;
constexpr int SM_GU = SM_O + 64;
constexpr int SM_MISC = SM_GU + 512;
constexpr int SM_BAR = SM_MISC + 128;
constexpr int SM_TOTAL = SM_BAR + 2 * NS * 8 + 512;
static_assert(SM_TOTAL <= 232448, "smem");

typedef unsigned long long u64;
struct Scratch {
    u64 x1[NCTA][256];
    u64 x2[NCTA][128];
    ulonglong2 x2ml[NCTA][2];
    ulonglong2 x3[NCTA][NCTA][2];
    unsigned epoch;
    unsigned pad[31];
    unsigned prog;
};
__device__ Scratch g_s;

#define TS(i) do {} while (0)

constexpr unsigned SPIN_LIMIT = 1u << 24;

__device__ __forceinline__ uint32_t s2u(const void* p) { return (uint32_t)__cvta_generic_to_shared(p); }
__device__ __forceinline__ void mbar_init(uint32_t a, int c) {
    asm volatile("mbarrier.init.shared::cta.b64 [%0], %1;" ::"r"(a), "r"(c) : "memory");
}
__device__ __forceinline__ void mbar_expect(uint32_t a, uint32_t b) {
    asm volatile("mbarrier.arrive.expect_tx.shared::cta.b64 _, [%0], %1;" ::"r"(a), "r"(b) : "memory");
}
__device__ __forceinline__ void mbar_arrive(uint32_t a) {
    asm volatile("mbarrier.arrive.shared::cta.b64 _, [%0];" ::"r"(a) : "memory");
}
__device__ __forceinline__ uint32_t mbar_try(uint32_t a, uint32_t ph) {
    uint32_t ok;
    asm volatile("{\n.reg .pred p;\nmbarrier.try_wait.parity.shared::cta.b64 p, [%1], %2, 200;\nselp.u32 %0, 1, 0, p;\n}"
                 : "=r"(ok) : "r"(a), "r"(ph) : "memory");
    return ok;
}
__device__ __forceinline__ void mbar_wait(uint32_t a, uint32_t ph, int en = 1) {
    uint32_t ok, n = 0;
    do {
        asm volatile("{\n.reg .pred p, q;\nsetp.eq.s32 p, %3, 0;\nsetp.ne.s32 q, %3, 0;\n"
                     "@q mbarrier.try_wait.parity.shared::cta.b64 p, [%1], %2;\nselp.u32 %0, 1, 0, p;\n}"
                     : "=r"(ok) : "r"(a), "r"(ph), "r"(en) : "memory");
        if (++n > (1u << 22)) __trap();
    } while (!ok);
}
__device__ __forceinline__ void bulk_ld(uint32_t dst, const void* src, uint32_t bytes, uint32_t bar) {
    asm volatile("cp.async.bulk.shared::cluster.global.mbarrier::complete_tx::bytes [%0], [%1], %2, [%3];"
                 ::"r"(dst), "l"(src), "r"(bytes), "r"(bar) : "memory");
}
__device__ __forceinline__ void ldg_nc(uint4& v, const void* a, int p) {
    asm volatile("{\n.reg .pred p;\nsetp.ne.s32 p, %5, 0;\n@p ld.global.nc.L1::no_allocate.v4.u32 {%0,%1,%2,%3}, [%4];\n}"
                 : "+r"(v.x), "+r"(v.y), "+r"(v.z), "+r"(v.w) : "l"(a), "r"(p));
}
__device__ __forceinline__ uint4 lds128(uint32_t a) {
    uint4 v;
    asm volatile("ld.shared.v4.u32 {%0,%1,%2,%3}, [%4];" : "=r"(v.x), "=r"(v.y), "=r"(v.z), "=r"(v.w) : "r"(a));
    return v;
}
__device__ __forceinline__ float2 lds64f(uint32_t a) {
    float2 v;
    asm volatile("ld.shared.v2.f32 {%0,%1}, [%2];" : "=f"(v.x), "=f"(v.y) : "r"(a));
    return v;
}
__device__ __forceinline__ float lds32f(uint32_t a) {
    float v;
    asm volatile("ld.shared.f32 %0, [%1];" : "=f"(v) : "r"(a));
    return v;
}
__device__ __forceinline__ void sts128f(uint32_t a, const float (&c)[4], int p) {
    asm volatile("{\n.reg .pred p;\nsetp.ne.s32 p, %5, 0;\n@p st.shared.v4.f32 [%0], {%1,%2,%3,%4};\n}"
                 ::"r"(a), "f"(c[0]), "f"(c[1]), "f"(c[2]), "f"(c[3]), "r"(p) : "memory");
}
__device__ __forceinline__ u64 pk(float v, unsigned tag) { return ((u64)tag << 32) | __float_as_uint(v); }
__device__ __forceinline__ float pk_val(u64 p) { return __uint_as_float((unsigned)p); }
__device__ __forceinline__ bool pk_ok(u64 p, unsigned tag) { return (unsigned)(p >> 32) == tag; }
__device__ __forceinline__ void ld_pk(u64& v, const void* a, int p) {
    asm volatile("{\n.reg .pred p;\nsetp.ne.s32 p, %2, 0;\n@p ld.relaxed.gpu.global.b64 %0, [%1];\n}"
                 : "+l"(v) : "l"(a), "r"(p) : "memory");
}
__device__ __forceinline__ void ld_pk2(ulonglong2& v, const void* a, int p) {
    asm volatile("{\n.reg .pred p;\nsetp.ne.s32 p, %3, 0;\n@p ld.relaxed.gpu.global.v2.b64 {%0,%1}, [%2];\n}"
                 : "+l"(v.x), "+l"(v.y) : "l"(a), "r"(p) : "memory");
}
__device__ __forceinline__ void st_pk(void* a, float v, unsigned tag, int p) {
    asm volatile("{\n.reg .pred p;\nsetp.ne.s32 p, %2, 0;\n@p st.relaxed.gpu.global.b64 [%0], %1;\n}"
                 ::"l"(a), "l"(pk(v, tag)), "r"(p) : "memory");
}
__device__ __forceinline__ void st_pk2(void* a, float v0, float v1, unsigned tag, int p) {
    asm volatile("{\n.reg .pred p;\nsetp.ne.s32 p, %3, 0;\n@p st.relaxed.gpu.global.v2.b64 [%0], {%1,%2};\n}"
                 ::"l"(a), "l"(pk(v0, tag)), "l"(pk(v1, tag)), "r"(p) : "memory");
}
__device__ __forceinline__ void mma16816(float (&c)[4], uint32_t a0, uint32_t a1, uint32_t a2, uint32_t a3,
                                         uint32_t b0, uint32_t b1) {
    asm volatile("mma.sync.aligned.m16n8k16.row.col.f32.bf16.bf16.f32 {%0,%1,%2,%3}, {%4,%5,%6,%7}, {%8,%9}, {%0,%1,%2,%3};"
                 : "+f"(c[0]), "+f"(c[1]), "+f"(c[2]), "+f"(c[3])
                 : "r"(a0), "r"(a1), "r"(a2), "r"(a3), "r"(b0), "r"(b1));
}
__device__ __forceinline__ void gemv_mma(float (&acc)[2][4], const uint4& L0, const uint4& L1, uint32_t b0, uint32_t b1) {
    mma16816(acc[0], L0.x, L0.y, L1.x, L1.y, b0, b1);
    mma16816(acc[1], L0.z, L0.w, L1.z, L1.w, b0, b1);
}
__device__ __forceinline__ float ex2(float x) {
    float y; asm("ex2.approx.ftz.f32 %0, %1;" : "=f"(y) : "f"(x)); return y;
}
__device__ __forceinline__ float bf16r(float x) { return __bfloat162float(__float2bfloat16_rn(x)); }
__device__ __forceinline__ uint32_t pack_bf16(float lo, float hi) {
    uint32_t r; asm("cvt.rn.bf16x2.f32 %0, %1, %2;" : "=r"(r) : "f"(hi), "f"(lo)); return r;
}
template <int ID, int N>
__device__ __forceinline__ void bar_sync(int p = 1) {
    asm volatile("{\n.reg .pred p;\nsetp.ne.s32 p, %0, 0;\n@p bar.sync %1, %2;\n}" ::"r"(p), "n"(ID), "n"(N) : "memory");
}
__device__ __forceinline__ int opaque(int v) { asm volatile("" : "+r"(v)); return v; }
__device__ __forceinline__ float sel4(int t, float a, float b, float c, float d) {
    return (t & 2) ? ((t & 1) ? d : c) : ((t & 1) ? b : a);
}

__device__ __forceinline__ float gather_x1(u64 (&p)[4], int h, int idx, unsigned tag) {
    unsigned n = 0;
    bool ok;
    do {
        ok = true;
#pragma unroll
        for (int i = 0; i < 4; i++) ld_pk(p[i], &g_s.x1[h * 4 + i][idx], !pk_ok(p[i], tag));
#pragma unroll
        for (int i = 0; i < 4; i++) ok = ok && pk_ok(p[i], tag);
        if (++n > SPIN_LIMIT) __trap();
    } while (!ok);
    return (pk_val(p[0]) + pk_val(p[1])) + (pk_val(p[2]) + pk_val(p[3]));
}

__global__ void __launch_bounds__(NTHREADS, 1)
fused_kernel(const __nv_bfloat16* __restrict__ x, const __nv_bfloat16* __restrict__ kc,
             const __nv_bfloat16* __restrict__ vc, const __nv_bfloat16* __restrict__ wq,
             const __nv_bfloat16* __restrict__ wo, const __nv_bfloat16* __restrict__ wg,
             const __nv_bfloat16* __restrict__ wu, const __nv_bfloat16* __restrict__ wd,
             const __nv_bfloat16* __restrict__ gate_w, __nv_bfloat16* __restrict__ out) {
    extern __shared__ __align__(1024) unsigned char smem[];
    const uint32_t sb = s2u(smem);
    const int tid = threadIdx.x, lane = tid & 31;
    const int cta = blockIdx.x, h = cta >> 2, s = cta & 3;
    const uint32_t fullb = sb + SM_BAR, emptyb = sb + SM_BAR + NS * 8;
    const size_t kvoff = (size_t)cta * (KEYS_CTA * DH * 2);
    if (__builtin_expect(tid == NW * 32, 1)) {
#pragma unroll
        for (int i = 0; i < WIN; i++) mbar_init(fullb + i * 8, 1);
        asm volatile("fence.mbarrier_init.release.cluster;" ::: "memory");
#pragma unroll
        for (int i = 0; i < WIN; i++) {
            mbar_expect(fullb + i * 8, TT_BYTES);
            bulk_ld(sb + SM_RING + i * SLOT_BYTES, reinterpret_cast<const unsigned char*>(kc) + kvoff + i * TT_BYTES, TT_BYTES, fullb + i * 8);
        }
        TS(5);
    }
    const int w = __shfl_sync(0xffffffffu, tid >> 5, 0);
    const int g = lane >> 2, t = lane & 3;
    float* misc = reinterpret_cast<float*>(smem + SM_MISC);
    volatile int* ctl = reinterpret_cast<volatile int*>(smem + SM_MISC) + 18;
    const int nch = h < 12 ? 6 : 5;
    const int ch0 = h < 12 ? 6 * h : 72 + 5 * (h - 12);

    const int r0 = 128 * s + 16 * w + 4 * t;
    uint4 fq[2][2][2] = {};
    uint2 xw = make_uint2(0, 0);
    u64 px[4] = {};
    unsigned tag;
    {
        const __nv_bfloat16* p = wq + (size_t)r0 * (NH * DH) + h * DH + g * 8;
        const int con = w < NW;
#pragma unroll
        for (int grp = 0; grp < 2; grp++)
#pragma unroll
            for (int r = 0; r < 2; r++)
#pragma unroll
                for (int win = 0; win < 2; win++)
                    ldg_nc(fq[grp][win][r], p + (size_t)(2 * grp + r) * (NH * DH) + win * 64, con);
        asm volatile("{\n.reg .pred p;\nsetp.ne.s32 p, %3, 0;\n@p ld.global.nc.v2.u32 {%0,%1}, [%2];\n}"
                     : "+r"(xw.x), "+r"(xw.y) : "l"(x + r0), "r"(con));
        asm volatile("ld.relaxed.gpu.global.u32 %0, [%1];" : "=r"(tag) : "l"(&g_s.epoch) : "memory");
#pragma unroll
        for (int i = 0; i < 4; i++) ld_pk(px[i], &g_s.x1[h * 4 + i][tid & 255], tid < 128);
    }

    if (__builtin_expect(w == NW, 0)) {
        if (lane == 0) {
#pragma unroll
            for (int i = WIN; i < NS; i++) mbar_init(fullb + i * 8, 1);
#pragma unroll
            for (int i = 0; i < NS; i++) mbar_init(emptyb + i * 8, TW);
            ctl[1] = WIN;
            ctl[2] = 0;
            asm volatile("fence.mbarrier_init.release.cluster;" ::: "memory");
        }
        __syncwarp();
        asm volatile("bar.arrive 3, %0;" ::"n"(NW * 32 + 32) : "memory");
        if (lane != 0) return;
        const unsigned char* src = reinterpret_cast<const unsigned char*>(kc) + kvoff + WIN * TT_BYTES;
        int slot = WIN, lslot = 0, landed = 0;
        uint32_t eph = 1, lph = 0, spins = 0;
#pragma unroll 1
        for (int j = WIN; j < NTT + 3; j++) {
            if (j == NTT / 2) src = reinterpret_cast<const unsigned char*>(vc) + kvoff;
            mbar_wait(emptyb + slot * 8, eph);
            while (landed < min(j, NTT) + 1 - ctl[1]) {
                if (!mbar_try(fullb + lslot * 8, lph)) { if (++spins > SPIN_LIMIT) __trap(); continue; }
                landed++;
                asm volatile("red.relaxed.gpu.global.add.u32 [%0], 1;" ::"l"(&g_s.prog) : "memory");
                ctl[2] = landed;
                if (++lslot == NS) { lslot = 0; lph ^= 1; }
            }
            int n = 1, bytes = TT_BYTES;
            if (j >= NTT) {
                n = (j > NTT || s + 4 >= nch) ? 4 : 8;
                bytes = j > NTT ? 4096 : 2048;
                src = j > NTT ? reinterpret_cast<const unsigned char*>(wo + (size_t)(h * DH + 32 * s + (j - NTT - 1) * 16) * D_MODEL)
                              : reinterpret_cast<const unsigned char*>(wd + (size_t)(8 * (ch0 + s)) * D_MODEL);
            }
            uint32_t dst = sb + SM_RING + slot * SLOT_BYTES;
            const uint32_t bar = fullb + slot * 8;
            mbar_expect(bar, n * bytes);
#pragma unroll 1
            for (int i = 0; i < n; i++) {
                bulk_ld(dst, src + i * bytes + (i >= 4 ? 24576 : 0), bytes, bar);
                dst += bytes + 32;
            }
            if (j == NTT - FLAG_AT) ctl[0] = 1;
            src += TT_BYTES;
            if (++slot == NS) { slot = 0; eph ^= 1; }
        }
        asm volatile("red.relaxed.gpu.global.add.u32 [%0], %1;" ::"l"(&g_s.prog), "r"(NTT - landed) : "memory");
        return;
    }

    const uint32_t selR0 = (g & 1) ? 0x1044u : 0x4410u;
    const uint32_t selR1 = (g & 1) ? 0x3244u : 0x4432u;
    float acc[2][2][4] = {};
    float m = 0.f;
    tag += 1;

    if (__builtin_expect(w < NW, 1)) {
        uint4 fg[2][2][2] = {};
        {
            const size_t off = (size_t)r0 * FF + (ch0 + g) * 8;
            const int ok = g < nch;
#pragma unroll
            for (int grp = 0; grp < 2; grp++)
#pragma unroll
                for (int r = 0; r < 2; r++) {
                    ldg_nc(fg[grp][0][r], wg + off + (size_t)(2 * grp + r) * FF, ok);
                    ldg_nc(fg[grp][1][r], wu + off + (size_t)(2 * grp + r) * FF, ok);
                }
        }
        uint32_t bx[2][2];
        const uint32_t rquart = sb + SM_RED + w * RED_WSTRIDE + g * 32 + (t >> 1) * 256 + (t & 1) * 16;
        {
            float aq[2][2][4] = {}, v[4];
#pragma unroll
            for (int grp = 0; grp < 2; grp++) {
                const uint32_t c = grp ? xw.y : xw.x;
                bx[grp][0] = __byte_perm(c, 0, selR0); bx[grp][1] = __byte_perm(c, 0, selR1);
#pragma unroll
                for (int win = 0; win < 2; win++) gemv_mma(aq[win], fq[grp][win][0], fq[grp][win][1], bx[grp][0], bx[grp][1]);
            }
#pragma unroll
            for (int e = 0; e < 4; e++) v[e] = sel4(t, aq[0][0][e], aq[0][1][e], aq[1][0][e], aq[1][1][e]);
            sts128f(rquart, v, 1);
        }
        if (tid == 0) TS(1);
        bar_sync<1, NW * 32>();
        if (tid < 128) {
            float v = 0.f;
#pragma unroll
            for (int i = 0; i < NW; i++) v += lds32f(sb + SM_RED + i * RED_WSTRIDE + tid * 4);
            st_pk(&g_s.x1[cta][tid], v, tag, 1);
            v = gather_x1(px, h, tid, tag);
            reinterpret_cast<__nv_bfloat16*>(smem + SM_Q)[tid] = __float2bfloat16_rn(v);
        }
        bar_sync<3, NW * 32 + 32>();
        if (tid == 0) TS(2);

        uint4 qf[4];
#pragma unroll
        for (int c = 0; c < 4; c++) qf[c] = lds128(sb + SM_Q + (t + 4 * (c ^ (g & 1))) * 16);
        constexpr float SCALE_LOG2E = 0.08838834764831845f * 1.4426950408889634f;
        float mx = -INFINITY;
        float* ss = reinterpret_cast<float*>(smem + SM_RED + w * RED_WSTRIDE + 1024) + lane;
        int slot = w / TW;
        uint32_t ph = 0;
        const uint32_t ring = sb + SM_RING + (w % TW) * WT_BYTES;
#pragma unroll 1
        for (int i = 0; i < TPW; i++) {
            mbar_wait(fullb + slot * 8, ph);
            const uint32_t tb = ring + slot * SLOT_BYTES + g * 256;
            float c0[4] = {}, c1[4] = {};
#pragma unroll
            for (int c = 0; c < 4; c++) {
                const uint32_t a = tb + (t + 4 * (c ^ (g & 1))) * 16;
                const uint4 A0 = lds128(a), A1 = lds128(a + 8 * 256), A2 = lds128(a + 16 * 256), A3 = lds128(a + 24 * 256);
                mma16816(c0, A0.x, A1.x, A0.y, A1.y, qf[c].x, qf[c].y);
                mma16816(c1, A2.x, A3.x, A2.y, A3.y, qf[c].x, qf[c].y);
                mma16816(c0, A0.z, A1.z, A0.w, A1.w, qf[c].z, qf[c].w);
                mma16816(c1, A2.z, A3.z, A2.w, A3.w, qf[c].z, qf[c].w);
            }
            __syncwarp();
            if (lane == 0) mbar_arrive(emptyb + slot * 8);
            const int o = g & 1;
            const float sc = sel4(t, o ? c0[1] : c0[0], o ? c0[3] : c0[2], o ? c1[1] : c1[0], o ? c1[3] : c1[2]) * SCALE_LOG2E;
            ss[i * 32] = sc;
            mx = fmaxf(mx, sc);
            slot += NW / TW;
            if (slot >= NS) { slot -= NS; ph ^= 1; }
        }
#pragma unroll
        for (int o = 16; o; o >>= 1) mx = fmaxf(mx, __shfl_xor_sync(0xffffffffu, mx, o));
        if (lane == 0) misc[w] = mx;
        {
            float ag[2][2][4] = {}, v[4];
#pragma unroll
            for (int grp = 0; grp < 2; grp++)
#pragma unroll
                for (int mm = 0; mm < 2; mm++) gemv_mma(ag[mm], fg[grp][mm][0], fg[grp][mm][1], bx[grp][0], bx[grp][1]);
#pragma unroll
            for (int e = 0; e < 4; e++) v[e] = sel4(t, ag[0][0][e], ag[0][1][e], ag[1][0][e], ag[1][1][e]);
            sts128f(rquart + 512, v, 1);
        }
        bar_sync<1, NW * 32>();
        if (tid == 0) TS(3);
        if (tid >= 128) {
            float v = 0.f;
#pragma unroll
            for (int i = 0; i < NW; i++) v += lds32f(sb + SM_RED + i * RED_WSTRIDE + tid * 4);
            st_pk(&g_s.x1[cta][tid], v, tag, 1);
        }
        {
            const float4 a = *reinterpret_cast<const float4*>(misc), b = *reinterpret_cast<const float4*>(misc + 4);
            m = fmaxf(fmaxf(fmaxf(a.x, a.y), fmaxf(a.z, a.w)), fmaxf(fmaxf(b.x, b.y), fmaxf(b.z, b.w)));
            __nv_bfloat16* pp = reinterpret_cast<__nv_bfloat16*>(smem + SM_P) + w * (TPW * 32) + 8 * t + g;
            float l = 0.f;
#pragma unroll
            for (int i = 0; i < TPW; i++) {
                const __nv_bfloat16 p = __float2bfloat16_rn(ex2(ss[i * 32] - m));
                pp[i * 32] = p;
                l += __bfloat162float(p);
            }
#pragma unroll
            for (int o = 16; o; o >>= 1) l += __shfl_xor_sync(0xffffffffu, l, o);
            if (lane == 0) misc[8 + w] = l;
            __syncwarp();
        }

        const bool actP = (g >> 1) == t;
        const uint32_t selP0 = actP ? selR0 : 0x4444u;
        const uint32_t selP1 = actP ? selR1 : 0x4444u;
        const uint32_t voff = (8 * t) * 256 + ((g + 2 * t) & 7) * 16;
#pragma unroll 1
        for (int i = 0; i < TPW; i++) {
            if (i == TPW / 2 && w >= 4) reinterpret_cast<float*>(smem + SM_GU)[tid - 128] = bf16r(gather_x1(px, h, tid, tag));
            const uint4 pf = lds128(sb + SM_P + (w * (TPW * 32) + i * 32 + 8 * t) * 2);
            mbar_wait(fullb + slot * 8, ph);
            const uint32_t tb = ring + slot * SLOT_BYTES + voff;
            const uint32_t pw[4] = {pf.x, pf.y, pf.z, pf.w};
#pragma unroll
            for (int grp = 0; grp < 4; grp++) {
                const uint32_t b0 = __byte_perm(pw[grp], 0, selP0), b1 = __byte_perm(pw[grp], 0, selP1);
                const uint32_t a = tb + grp * 512;
                const uint4 A0 = lds128(a), A1 = lds128(a + 256), A2 = lds128(a + 128), A3 = lds128(a + 256 + 128);
                gemv_mma(acc[0], A0, A1, b0, b1);
                gemv_mma(acc[1], A2, A3, b0, b1);
            }
            __syncwarp();
            if (lane == 0) mbar_arrive(emptyb + slot * 8);
            slot += NW / TW;
            if (slot >= NS) { slot -= NS; ph ^= 1; }
        }
        if (lane == 0) { if (w == 0) TS(4); if (w == 7) TS(12); }
    } else {
        if (lane == 0) ctl[0] = 0;
        uint4 xa = {}, xb = {}, ga = {}, gb = {};
        ldg_nc(xa, x + lane * 16, 1); ldg_nc(xb, x + lane * 16 + 8, 1);
        ldg_nc(ga, gate_w + lane * 16, 1); ldg_nc(gb, gate_w + lane * 16 + 8, 1);
        const uint32_t xr[8] = {xa.x, xa.y, xa.z, xa.w, xb.x, xb.y, xb.z, xb.w};
        const uint32_t gr[8] = {ga.x, ga.y, ga.z, ga.w, gb.x, gb.y, gb.z, gb.w};
        float a = 0.f;
#pragma unroll
        for (int i = 0; i < 8; i++) {
            a += bf16r(__uint_as_float(xr[i] << 16) * __uint_as_float(gr[i] << 16));
            a += bf16r(__uint_as_float(xr[i] & 0xffff0000u) * __uint_as_float(gr[i] & 0xffff0000u));
        }
#pragma unroll
        for (int o = 16; o; o >>= 1) a += __shfl_xor_sync(0xffffffffu, a, o);
        a = bf16r(a);
        const float gate = bf16r(1.f / (1.f + __expf(-a)));
        if (lane == 0) {
            misc[16] = gate;
            misc[17] = bf16r(1.f - gate);
        }
    }

    const int is_aux = opaque(w > NW);
    const int col = tid >> 1, half = tid & 1;
#pragma unroll 1
    for (int pass = (is_aux && WARM) ? 0 : 1; pass < 2; pass++) {
        const int real = opaque(pass);
        const int con = opaque(!is_aux);
        float af[2][4] = {};
        uint4 fo[4][2] = {};
        if (con || !real) {
            const uint32_t a = sb + SM_RED + w * RED_WSTRIDE + t * 512 + (t >> 1) * 16 + ((g + 2 * t) & 7) * 32;
            sts128f(a, acc[0][0], con); sts128f(a + 16, acc[0][1], con);
            sts128f(a + 256, acc[1][0], con); sts128f(a + 256 + 16, acc[1][1], con);
            bar_sync<1, NW * 32>(con);
            float v[4];
            const uint32_t rp = sb + SM_RED + half * (4 * RED_WSTRIDE) + col * 4;
#pragma unroll
            for (int i = 0; i < 4; i++)
                v[i] = (lds32f(rp + i * RED_WSTRIDE) + lds32f(rp + i * RED_WSTRIDE + 512)) +
                       (lds32f(rp + i * RED_WSTRIDE + 1024 + 16) + lds32f(rp + i * RED_WSTRIDE + 1536 + 16));
            float vs = (v[0] + v[1]) + (v[2] + v[3]);
            vs += __shfl_xor_sync(0xffffffffu, vs, 1);
            st_pk(&g_s.x2[cta][col & 127], vs, tag, con && half == 0);
            {
                const float4 la = *reinterpret_cast<const float4*>(misc + 8), lb = *reinterpret_cast<const float4*>(misc + 12);
                st_pk2(&g_s.x2ml[cta][tid & 1], m, ((la.x + la.y) + (la.z + la.w)) + ((lb.x + lb.y) + (lb.z + lb.w)), tag, tid < 2);
            }
            if (tid == 0) TS(6);
            const uint32_t wa = sb + SM_RING + (w & 7) * 128 + g * 16;
            mbar_wait(fullb + (NTT % NS) * 8, (NTT / NS) & 1, con);
#pragma unroll
            for (int ci = 0; ci < 2; ci++) {
                if (ci == 0 || s + 4 < nch) {
                    const int f = 8 * (s + 4 * ci) + 2 * t;
                    const float2 gg = lds64f(sb + SM_GU + f * 4), uu = lds64f(sb + SM_GU + 256 + f * 4);
                    const uint32_t hf = pack_bf16(gg.x * uu.x, gg.y * uu.y);
                    const uint32_t a0 = wa + (NTT % NS) * SLOT_BYTES + (4 * ci + t) * 2080;
                    gemv_mma(af, lds128(a0), lds128(a0 + 1024), __byte_perm(hf, 0, selR0), __byte_perm(hf, 0, selR1));
                }
            }
#pragma unroll
            for (int k = 0; k < 2; k++) {
                mbar_wait(fullb + ((NTT + 1 + k) % NS) * 8, ((NTT + 1 + k) / NS) & 1, con);
                const uint32_t a0 = wa + ((NTT + 1 + k) % NS) * SLOT_BYTES + t * 4128;
                fo[2 * k][0] = lds128(a0);
                fo[2 * k][1] = lds128(a0 + 1024);
                fo[2 * k + 1][0] = lds128(a0 + 2048);
                fo[2 * k + 1][1] = lds128(a0 + 3072);
            }
            if (tid == 0) TS(13);
        }
        ulonglong2 e[8];
        const ulonglong2* src3 = &g_s.x3[cta][lane >> 1][lane & 1];
        const u64 okp = pk(0.f, tag);
        if (is_aux) {
            unsigned n = 0;
            if (real) {
                while (ctl[0] == 0) {
                    const int own0 = ctl[2];
                    unsigned G;
                    asm volatile("ld.relaxed.gpu.global.u32 %0, [%1];" : "=r"(G) : "l"(&g_s.prog) : "memory");
                    G -= (tag - 1) * (unsigned)(NCTA * NTT);
                    const int own1 = ctl[2];
                    const int lead = (own0 + own1) * (NCTA / 2) - (int)G;
                    const int win = WIN + (lead > 2 * FB ? -2 : lead > FB ? -1 : lead < -2 * FB ? 2 : lead < -FB ? 1 : 0);
                    if (lane == 0 && own1 >= 8) ctl[1] = win;
                    __nanosleep(200);
                    if (++n > SPIN_LIMIT) __trap();
                }
            }
#pragma unroll
            for (int k = 0; k < 8; k++) {
                e[k].x = e[k].y = okp;
                ld_pk2(e[k], src3 + k * 32, real);
            }
            u64 o4[4];
            ulonglong2 ml[4];
            const u64* src = &g_s.x2[h * 4][32 * s + lane];
            bool ok;
            do {
                ok = true;
#pragma unroll
                for (int i = 0; i < 4; i++) {
                    o4[i] = ml[i].x = ml[i].y = okp;
                    ld_pk(o4[i], src + i * 128, real);
                    ld_pk2(ml[i], &g_s.x2ml[h * 4 + i][0], real);
                }
#pragma unroll
                for (int i = 0; i < 4; i++) ok = ok && pk_ok(o4[i], tag) && pk_ok(ml[i].x, tag) && pk_ok(ml[i].y, tag);
                if (++n > SPIN_LIMIT) __trap();
            } while (!ok);
            const float M = fmaxf(fmaxf(pk_val(ml[0].x), pk_val(ml[1].x)), fmaxf(pk_val(ml[2].x), pk_val(ml[3].x)));
            float den = 0.f, num = 0.f;
#pragma unroll
            for (int i = 0; i < 4; i++) {
                const float wt = ex2(pk_val(ml[i].x) - M);
                den += wt * pk_val(ml[i].y);
                num += wt * pk_val(o4[i]);
            }
            const uint32_t p0 = pack_bf16(__fdividef(num, den), 0.f);
            asm volatile("{\n.reg .pred p;\nsetp.ne.s32 p, %2, 0;\n@p st.shared.u16 [%0], %1;\n}"
                         ::"r"(sb + SM_O + (((lane >> 2) & 3) * 8 + (lane >> 4) * 4 + (lane & 3)) * 2), "h"((unsigned short)p0), "r"(real) : "memory");
            if (real && lane == 0) TS(10);
        }
        bar_sync<2, NW * 32 + 32>(real);
        if (con || !real) {
            const uint4 ow = lds128(sb + SM_O + t * 16);
            const float2 gt = lds64f(sb + SM_MISC + 64);
            const uint32_t oc[4] = {ow.x, ow.y, ow.z, ow.w};
            float a0[2][4] = {}, a1[2][4] = {};
#pragma unroll
            for (int grp = 0; grp < 4; grp++)
                gemv_mma((grp & 1) ? a1 : a0, fo[grp][0], fo[grp][1], __byte_perm(oc[grp], 0, selR0), __byte_perm(oc[grp], 0, selR1));
            float r[2][4];
#pragma unroll
            for (int j = 0; j < 2; j++)
#pragma unroll
                for (int q = 0; q < 4; q++) r[j][q] = gt.x * (a0[j][q] + a1[j][q]) + gt.y * af[j][q];
            st_pk2(&g_s.x3[(16 * w + 2 * g + (t >> 1)) & (NCTA - 1)][cta][t & 1],
                   sel4(t, r[0][0], r[0][2], r[1][0], r[1][2]), sel4(t, r[0][1], r[0][3], r[1][1], r[1][3]), tag, con);
            if (tid == 0) TS(7);
        }
        if (is_aux) {
            unsigned n = 0;
            bool ok;
            do {
                ok = true;
#pragma unroll
                for (int k = 0; k < 8; k++) ld_pk2(e[k], src3 + k * 32, !(pk_ok(e[k].x, tag) && pk_ok(e[k].y, tag)));
#pragma unroll
                for (int k = 0; k < 8; k++) ok = ok && pk_ok(e[k].x, tag) && pk_ok(e[k].y, tag);
                if (++n > SPIN_LIMIT) __trap();
            } while (!ok);
            float v0 = ((pk_val(e[0].x) + pk_val(e[1].x)) + (pk_val(e[2].x) + pk_val(e[3].x))) +
                       ((pk_val(e[4].x) + pk_val(e[5].x)) + (pk_val(e[6].x) + pk_val(e[7].x)));
            float v1 = ((pk_val(e[0].y) + pk_val(e[1].y)) + (pk_val(e[2].y) + pk_val(e[3].y))) +
                       ((pk_val(e[4].y) + pk_val(e[5].y)) + (pk_val(e[6].y) + pk_val(e[7].y)));
            __syncwarp();
#pragma unroll
            for (int o = 16; o > 1; o >>= 1) {
                v0 += __shfl_xor_sync(0xffffffffu, v0, o);
                v1 += __shfl_xor_sync(0xffffffffu, v1, o);
            }
            asm volatile("{\n.reg .pred p;\nsetp.ne.s32 p, %2, 0;\n@p st.global.u32 [%0], %1;\n}"
                         ::"l"(out + cta * 4 + (lane & 1) * 2), "r"(pack_bf16(v0, v1)), "r"((int)(real && lane < 2)) : "memory");
            asm volatile("{\n.reg .pred p;\nsetp.ne.s32 p, %2, 0;\n@p st.global.u32 [%0], %1;\n}"
                         ::"l"(&g_s.epoch), "r"(tag), "r"((int)(real && lane == 0 && cta == 0)) : "memory");
            if (lane == 0) TS(8 + real);
        }
    }
}

}

extern "C" void kernel_launch(void* const* d_in, const int* in_sizes, int n_in, void* d_out, int out_size) {
    (void)in_sizes; (void)n_in; (void)out_size;
    static bool init = false;
    if (!init) {
        cudaFuncSetAttribute(fused_kernel, cudaFuncAttributeMaxDynamicSharedMemorySize, SM_TOTAL);
        init = true;
    }
    fused_kernel<<<NCTA, NTHREADS, SM_TOTAL>>>(
        (const __nv_bfloat16*)d_in[0], (const __nv_bfloat16*)d_in[1], (const __nv_bfloat16*)d_in[2],
        (const __nv_bfloat16*)d_in[3], (const __nv_bfloat16*)d_in[4], (const __nv_bfloat16*)d_in[6],
        (const __nv_bfloat16*)d_in[7], (const __nv_bfloat16*)d_in[8], (const __nv_bfloat16*)d_in[9],
        (__nv_bfloat16*)d_out);
}
```

```cpp
#include <cuda_runtime.h>
#include <cuda_bf16.h>
#include <stdint.h>

namespace {

constexpr int D_MODEL = 512;
constexpr int NH = 32;
constexpr int SK = 8192;
constexpr int DH = 128;
constexpr int FF = 1376;
constexpr int NSPLIT = 4;
constexpr int NCTA = NH * NSPLIT;
constexpr int KEYS_CTA = SK / NSPLIT;
constexpr int NW = 8;
constexpr int WT_BYTES = 32 * DH * 2;
constexpr int TW = 2;
constexpr int NS = 12;
constexpr int WIN = 4;
constexpr int FB = 160;
constexpr int FLAG_AT = 2;
constexpr int TT_BYTES = TW * WT_BYTES;
constexpr int SLOT_BYTES = TT_BYTES + 256;
constexpr int TPW = KEYS_CTA / 32 / NW;
constexpr int NTT = 2 * TPW * NW / TW;
constexpr int NTHREADS = NW * 32 + 64;

constexpr int SM_RING = 0;
constexpr int SM_RED = SM_RING + NS * SLOT_BYTES;
constexpr int RED_WSTRIDE = 2096;
constexpr int SM_SS = SM_RED;
constexpr int SM_P = SM_RED + NW * RED_WSTRIDE;
constexpr int SM_Q = SM_P + NW * TPW * 32 * 2;
constexpr int SM_O = SM_Q + 256;
constexpr int SM_GU = SM_O + 64;
constexpr int SM_MISC = SM_GU + 512;
constexpr int SM_BAR = SM_MISC + 128;
constexpr int SM_TOTAL = SM_BAR + 2 * NS * 8 + 512;
static_assert(SM_TOTAL <= 232448, "smem");

struct Scratch {
    uint2 x1[NCTA][256];
    uint2 x2[NCTA][128];
    uint4 x2ml[NCTA][2];
    uint4 x3[NCTA][NCTA][2];
    unsigned epoch;
    unsigned pad[31];
    unsigned prog;
};
__device__ Scratch g_s;

__device__ __forceinline__ uint32_t s2u(const void* p) { return (uint32_t)__cvta_generic_to_shared(p); }
__device__ __forceinline__ void mbar_init(uint32_t a, int c) {
    asm volatile("mbarrier.init.shared::cta.b64 [%0], %1;" ::"r"(a), "r"(c) : "memory");
}
__device__ __forceinline__ void mbar_expect(uint32_t a, uint32_t b) {
    asm volatile("mbarrier.arrive.expect_tx.shared::cta.b64 _, [%0], %1;" ::"r"(a), "r"(b) : "memory");
}
__device__ __forceinline__ void mbar_arrive(uint32_t a) {
    asm volatile("mbarrier.arrive.shared::cta.b64 _, [%0];" ::"r"(a) : "memory");
}
__device__ __forceinline__ void mbar_wait(uint32_t a, uint32_t ph) {
    uint32_t ok, n = 0;
    do {
        asm volatile("{\n.reg .pred p;\nmbarrier.try_wait.parity.shared::cta.b64 p, [%1], %2;\nselp.u32 %0, 1, 0, p;\n}"
                     : "=r"(ok) : "r"(a), "r"(ph) : "memory");
        if (++n > (1u << 22)) __trap();
    } while (!ok);
}
__device__ __forceinline__ uint32_t mbar_try(uint32_t a, uint32_t ph) {
    uint32_t ok;
    asm volatile("{\n.reg .pred p;\nmbarrier.try_wait.parity.shared::cta.b64 p, [%1], %2, 200;\nselp.u32 %0, 1, 0, p;\n}"
                 : "=r"(ok) : "r"(a), "r"(ph) : "memory");
    return ok;
}
__device__ __forceinline__ void mbar_wait_p(uint32_t a, uint32_t ph, int en) {
    uint32_t ok, n = 0;
    do {
        asm volatile("{\n.reg .pred p, q;\nsetp.eq.s32 p, %3, 0;\nsetp.ne.s32 q, %3, 0;\n@q mbarrier.try_wait.parity.shared::cta.b64 p, [%1], %2;\nselp.u32 %0, 1, 0, p;\n}"
                     : "=r"(ok) : "r"(a), "r"(ph), "r"(en) : "memory");
        if (++n > (1u << 22)) __trap();
    } while (!ok);
}
__device__ __forceinline__ void bulk_ld(uint32_t dst, const void* src, uint32_t bytes, uint32_t bar) {
    uint64_t pol;
    asm volatile("createpolicy.fractional.L2::evict_first.b64 %0, 1.0;" : "=l"(pol));
    asm volatile("cp.async.bulk.shared::cluster.global.mbarrier::complete_tx::bytes.L2::cache_hint [%0], [%1], %2, [%3], %4;"
                 ::"r"(dst), "l"(src), "r"(bytes), "r"(bar), "l"(pol) : "memory");
}
__device__ __forceinline__ uint4 ldg_nc(const void* p) {
    uint4 v;
    asm volatile("ld.global.nc.L1::no_allocate.v4.u32 {%0,%1,%2,%3}, [%4];"
                 : "=r"(v.x), "=r"(v.y), "=r"(v.z), "=r"(v.w) : "l"(p));
    return v;
}
__device__ __forceinline__ void ldg_nc_p(uint4& v, const void* a, int p) {
    uint64_t pol;
    asm volatile("createpolicy.fractional.L2::evict_first.b64 %0, 1.0;" : "=l"(pol));
    asm volatile("{\n.reg .pred p;\nsetp.ne.s32 p, %5, 0;\n@p ld.global.nc.L1::no_allocate.L2::cache_hint.v4.u32 {%0,%1,%2,%3}, [%4], %6;\n}"
                 : "+r"(v.x), "+r"(v.y), "+r"(v.z), "+r"(v.w) : "l"(a), "r"(p), "l"(pol));
}
__device__ __forceinline__ uint4 lds128(uint32_t a) {
    uint4 v;
    asm volatile("ld.shared.v4.u32 {%0,%1,%2,%3}, [%4];" : "=r"(v.x), "=r"(v.y), "=r"(v.z), "=r"(v.w) : "r"(a));
    return v;
}
__device__ __forceinline__ uint2 lds64(uint32_t a) {
    uint2 v;
    asm volatile("ld.shared.v2.u32 {%0,%1}, [%2];" : "=r"(v.x), "=r"(v.y) : "r"(a));
    return v;
}
__device__ __forceinline__ float lds32f(uint32_t a) {
    float v;
    asm volatile("ld.shared.f32 %0, [%1];" : "=f"(v) : "r"(a));
    return v;
}
__device__ __forceinline__ void sts128f_p(uint32_t a, const float (&c)[4], int p) {
    asm volatile("{\n.reg .pred p;\nsetp.ne.s32 p, %5, 0;\n@p st.shared.v4.f32 [%0], {%1,%2,%3,%4};\n}"
                 ::"r"(a), "f"(c[0]), "f"(c[1]), "f"(c[2]), "f"(c[3]), "r"(p) : "memory");
}
__device__ __forceinline__ void ld_ll2_p(uint2& v, const void* a, int p) {
    asm volatile("{\n.reg .pred p;\nsetp.ne.s32 p, %3, 0;\n@p ld.relaxed.gpu.global.v2.u32 {%0,%1}, [%2];\n}"
                 : "+r"(v.x), "+r"(v.y) : "l"(a), "r"(p) : "memory");
}
__device__ __forceinline__ void ld_ll4_p(uint4& v, const void* a, int p) {
    asm volatile("{\n.reg .pred p;\nsetp.ne.s32 p, %5, 0;\n@p ld.relaxed.gpu.global.v4.u32 {%0,%1,%2,%3}, [%4];\n}"
                 : "+r"(v.x), "+r"(v.y), "+r"(v.z), "+r"(v.w) : "l"(a), "r"(p) : "memory");
}
__device__ __forceinline__ void st_ll_p(uint2* a, float v, unsigned tag, int p) {
    asm volatile("{\n.reg .pred p;\nsetp.ne.s32 p, %3, 0;\n@p st.relaxed.gpu.global.v2.u32 [%0], {%1,%2};\n}"
                 ::"l"(a), "r"(__float_as_uint(v)), "r"(tag), "r"(p) : "memory");
}
__device__ __forceinline__ void st_ll4_p(void* a, float v0, float v1, unsigned tag, int p) {
    asm volatile("{\n.reg .pred p;\nsetp.ne.s32 p, %4, 0;\n@p st.relaxed.gpu.global.v4.u32 [%0], {%1,%2,%3,%2};\n}"
                 ::"l"(a), "r"(__float_as_uint(v0)), "r"(tag), "r"(__float_as_uint(v1)), "r"(p) : "memory");
}
__device__ __forceinline__ void mma16816(float (&c)[4], uint32_t a0, uint32_t a1, uint32_t a2, uint32_t a3,
                                         uint32_t b0, uint32_t b1) {
    asm volatile("mma.sync.aligned.m16n8k16.row.col.f32.bf16.bf16.f32 {%0,%1,%2,%3}, {%4,%5,%6,%7}, {%8,%9}, {%0,%1,%2,%3};"
                 : "+f"(c[0]), "+f"(c[1]), "+f"(c[2]), "+f"(c[3])
                 : "r"(a0), "r"(a1), "r"(a2), "r"(a3), "r"(b0), "r"(b1));
}
__device__ __forceinline__ void gemv_mma(float (&acc)[2][4], const uint4& L0, const uint4& L1, uint32_t b0, uint32_t b1) {
    mma16816(acc[0], L0.x, L0.y, L1.x, L1.y, b0, b1);
    mma16816(acc[1], L0.z, L0.w, L1.z, L1.w, b0, b1);
}
__device__ __forceinline__ float ex2(float x) {
    float y; asm("ex2.approx.ftz.f32 %0, %1;" : "=f"(y) : "f"(x)); return y;
}
__device__ __forceinline__ float bf16r(float x) { return __bfloat162float(__float2bfloat16_rn(x)); }
__device__ __forceinline__ uint32_t pack_bf16(float lo, float hi) {
    uint32_t r; asm("cvt.rn.bf16x2.f32 %0, %1, %2;" : "=r"(r) : "f"(hi), "f"(lo)); return r;
}
__device__ __forceinline__ void bar_sync(int id, int n) { asm volatile("bar.sync %0, %1;" ::"r"(id), "r"(n) : "memory"); }
template <int ID, int N>
__device__ __forceinline__ void bar_sync_p(int p) {
    asm volatile("{\n.reg .pred p;\nsetp.ne.s32 p, %0, 0;\n@p bar.sync %1, %2;\n}" ::"r"(p), "n"(ID), "n"(N) : "memory");
}
__device__ __forceinline__ int opaque(int v) { asm volatile("" : "+r"(v)); return v; }

constexpr unsigned SPIN_LIMIT = 1u << 24;

__device__ __forceinline__ float gather_x1(uint2 (&p)[4], int h, int idx, unsigned tag) {
    unsigned n = 0;
    bool ok;
    do {
        ok = true;
#pragma unroll
        for (int i = 0; i < 4; i++) ld_ll2_p(p[i], &g_s.x1[h * 4 + i][idx], p[i].y != tag);
#pragma unroll
        for (int i = 0; i < 4; i++) ok = ok && p[i].y == tag;
        if (!ok) __nanosleep(100);
        if (++n > SPIN_LIMIT) __trap();
    } while (!ok);
    return (__uint_as_float(p[0].x) + __uint_as_float(p[1].x)) + (__uint_as_float(p[2].x) + __uint_as_float(p[3].x));
}

__global__ void __launch_bounds__(NTHREADS, 1)
fused_kernel(const __nv_bfloat16* __restrict__ x, const __nv_bfloat16* __restrict__ kc,
             const __nv_bfloat16* __restrict__ vc, const __nv_bfloat16* __restrict__ wq,
             const __nv_bfloat16* __restrict__ wo, const __nv_bfloat16* __restrict__ wg,
             const __nv_bfloat16* __restrict__ wu, const __nv_bfloat16* __restrict__ wd,
             const __nv_bfloat16* __restrict__ gate_w, __nv_bfloat16* __restrict__ out) {
    extern __shared__ __align__(1024) unsigned char smem[];
    const uint32_t sb = s2u(smem);
    const int tid = threadIdx.x, lane = tid & 31;
    const int w = __shfl_sync(0xffffffffu, tid >> 5, 0);
    const int g = lane >> 2, t = lane & 3;
    const int cta = blockIdx.x, h = cta >> 2, s = cta & 3;
    float* misc = reinterpret_cast<float*>(smem + SM_MISC);
    const uint32_t fullb = sb + SM_BAR, emptyb = sb + SM_BAR + NS * 8;
    const int nch = h < 12 ? 6 : 5;
    const int ch0 = h < 12 ? 6 * h : 72 + 5 * (h - 12);

    const size_t kvoff = ((size_t)h * SK + (size_t)s * KEYS_CTA) * (DH * 2);
    if (__builtin_expect(tid == NW * 32, 1)) {
#pragma unroll
        for (int i = 0; i < WIN; i++) mbar_init(fullb + i * 8, 1);
        asm volatile("fence.mbarrier_init.release.cluster;" ::: "memory");
#pragma unroll
        for (int i = 0; i < WIN; i++) {
            mbar_expect(fullb + i * 8, TT_BYTES);
            bulk_ld(sb + SM_RING + i * SLOT_BYTES, reinterpret_cast<const unsigned char*>(kc) + kvoff + i * TT_BYTES, TT_BYTES, fullb + i * 8);
        }
    }
    const int r0 = 128 * s + 16 * w + 4 * t;
    uint4 fq[2][2][2] = {};
    uint2 xw = make_uint2(0, 0);
    uint2 px[4] = {};
    unsigned tag;
    {
        const __nv_bfloat16* p = wq + (size_t)r0 * (NH * DH) + h * DH + g * 8;
        const int con = w < NW;
#pragma unroll
        for (int grp = 0; grp < 2; grp++)
#pragma unroll
            for (int r = 0; r < 2; r++)
#pragma unroll
                for (int win = 0; win < 2; win++)
                    ldg_nc_p(fq[grp][win][r], p + (size_t)(2 * grp + r) * (NH * DH) + win * 64, con);
        asm volatile("{\n.reg .pred p;\nsetp.ne.s32 p, %3, 0;\n@p ld.global.nc.v2.u32 {%0,%1}, [%2];\n}"
                     : "+r"(xw.x), "+r"(xw.y) : "l"(x + r0), "r"(con));
        asm volatile("ld.relaxed.gpu.global.u32 %0, [%1];" : "=r"(tag) : "l"(&g_s.epoch) : "memory");
    }
    if (__builtin_expect(w == NW, 1)) {
        if (lane == 0) {
#pragma unroll
            for (int i = WIN; i < NS; i++) mbar_init(fullb + i * 8, 1);
#pragma unroll
            for (int i = 0; i < NS; i++) mbar_init(emptyb + i * 8, TW);
            *reinterpret_cast<volatile int*>(misc + 19) = WIN;
            *reinterpret_cast<volatile int*>(misc + 20) = 0;
            asm volatile("fence.mbarrier_init.release.cluster;" ::: "memory");
        }
        __syncwarp();
        asm volatile("bar.arrive 3, %0;" ::"n"(NW * 32 + 32) : "memory");
        const unsigned char* src = reinterpret_cast<const unsigned char*>(kc) + kvoff + WIN * TT_BYTES;
        int slot = WIN, lslot = 0, landed = 0;
        uint32_t eph = 1, lph = 0, spins = 0;
#pragma unroll 1
        for (int j = WIN; j < NTT + 3; j++) {
            if (j == NTT / 2) src = reinterpret_cast<const unsigned char*>(vc) + kvoff;
            mbar_wait(emptyb + slot * 8, eph);
            while (landed < min(NTT, (j < NTT ? j : NTT) + 1 - *reinterpret_cast<volatile int*>(misc + 19))) {
                if (!mbar_try(fullb + lslot * 8, lph)) { if (++spins > (1u << 24)) __trap(); continue; }
                landed++;
                if (lane == 0) {
                    asm volatile("red.relaxed.gpu.global.add.u32 [%0], 1;" ::"l"(&g_s.prog) : "memory");
                    *reinterpret_cast<volatile int*>(misc + 20) = landed;
                }
                if (++lslot == NS) { lslot = 0; lph ^= 1; }
            }
            int n = 1, bytes = TT_BYTES;
            if (j >= NTT) {
                n = (j > NTT || s + 4 >= nch) ? 4 : 8;
                bytes = j > NTT ? 4096 : 2048;
                src = j > NTT ? reinterpret_cast<const unsigned char*>(wo + (size_t)(h * DH + 32 * s + (j - NTT - 1) * 16) * D_MODEL)
                              : reinterpret_cast<const unsigned char*>(wd + (size_t)(8 * (ch0 + s)) * D_MODEL);
            }
            if (lane == 0) {
                uint32_t dst = sb + SM_RING + slot * SLOT_BYTES;
                const uint32_t bar = fullb + slot * 8;
                mbar_expect(bar, n * bytes);
#pragma unroll 1
                for (int i = 0; i < n; i++) {
                    bulk_ld(dst, src + i * bytes + (i >= 4 ? 24576 : 0), bytes, bar);
                    dst += bytes + 32;
                }
                if (j == NTT - FLAG_AT) *reinterpret_cast<volatile int*>(misc + 18) = 1;
            }
            src += TT_BYTES;
            if (++slot == NS) { slot = 0; eph ^= 1; }
        }
        if (lane == 0) asm volatile("red.relaxed.gpu.global.add.u32 [%0], %1;" ::"l"(&g_s.prog), "r"(NTT - landed) : "memory");
    }
    if (opaque(w) != NW) {

    const uint32_t selR0 = (g & 1) ? 0x1044u : 0x4410u;
    const uint32_t selR1 = (g & 1) ? 0x3244u : 0x4432u;

    float acc[2][2][4] = {};
    float m = 0.f;

    if (__builtin_expect(w < NW, 1)) {
        uint4 fg[2][2][2] = {};
        st_ll_p(&g_s.x1[cta][tid], 0.f, 0, 1);
        st_ll_p(&g_s.x2[cta][tid >> 1], 0.f, 0, !(tid & 1));
        st_ll4_p(&g_s.x2ml[cta][tid & 1], 0.f, 0.f, 0, tid < 2);
        st_ll4_p(&g_s.x3[16 * w + 2 * g + (t >> 1)][cta][t & 1], 0.f, 0.f, 0, 1);
        uint32_t bx[2][2];
        {
            float aq[2][2][4] = {};
#pragma unroll
            for (int grp = 0; grp < 2; grp++) {
                const uint32_t c = grp ? xw.y : xw.x;
                bx[grp][0] = __byte_perm(c, 0, selR0); bx[grp][1] = __byte_perm(c, 0, selR1);
#pragma unroll
                for (int win = 0; win < 2; win++) gemv_mma(aq[win], fq[grp][win][0], fq[grp][win][1], bx[grp][0], bx[grp][1]);
            }
            const uint32_t a = sb + SM_RED + w * RED_WSTRIDE + g * 32 + (t >> 1) * 256 + (t & 1) * 16;
            float v[4];
#pragma unroll
            for (int e = 0; e < 4; e++) v[e] = (t & 2) ? ((t & 1) ? aq[1][1][e] : aq[1][0][e]) : ((t & 1) ? aq[0][1][e] : aq[0][0][e]);
            sts128f_p(a, v, 1);
        }
        {
            const size_t off = (size_t)r0 * FF + (ch0 + g) * 8;
            const int ok = g < nch;
#pragma unroll
            for (int grp = 0; grp < 2; grp++)
#pragma unroll
                for (int r = 0; r < 2; r++) {
                    ldg_nc_p(fg[grp][0][r], wg + off + (size_t)(2 * grp + r) * FF, ok);
                    ldg_nc_p(fg[grp][1][r], wu + off + (size_t)(2 * grp + r) * FF, ok);
                }
        }
        tag += 1;
        bar_sync(1, NW * 32);
        if (tid < 128) {
            float v = 0.f;
#pragma unroll
            for (int i = 0; i < NW; i++) v += lds32f(sb + SM_RED + i * RED_WSTRIDE + tid * 4);
            st_ll_p(&g_s.x1[cta][tid], v, tag, 1);
            v = gather_x1(px, h, tid, tag);
            reinterpret_cast<__nv_bfloat16*>(smem + SM_Q)[tid] = __float2bfloat16_rn(v);
        }
        bar_sync(3, NW * 32 + 32);
        if (tid == 0) *reinterpret_cast<volatile int*>(misc + 19) = WIN;

        uint4 qf[4];
#pragma unroll
        for (int c = 0; c < 4; c++) qf[c] = lds128(sb + SM_Q + (t + 4 * (c ^ (g & 1))) * 16);
        constexpr float SCALE_LOG2E = 0.08838834764831845f * 1.4426950408889634f;
        float mx = -INFINITY;
        float* ss = reinterpret_cast<float*>(smem + SM_SS + w * RED_WSTRIDE + 1024) + lane;
        int slot = w / TW;
        uint32_t ph = 0;
        const uint32_t ring = sb + SM_RING + (w % TW) * WT_BYTES;
#pragma unroll 1
        for (int i = 0; i < TPW; i++) {
            mbar_wait(fullb + slot * 8, ph);
            const uint32_t tb = ring + slot * SLOT_BYTES + g * 256;
            float c0[4] = {}, c1[4] = {};
#pragma unroll
            for (int c = 0; c < 4; c++) {
                const uint32_t a = tb + (t + 4 * (c ^ (g & 1))) * 16;
                const uint4 A0 = lds128(a), A1 = lds128(a + 8 * 256), A2 = lds128(a + 16 * 256), A3 = lds128(a + 24 * 256);
                mma16816(c0, A0.x, A1.x, A0.y, A1.y, qf[c].x, qf[c].y);
                mma16816(c1, A2.x, A3.x, A2.y, A3.y, qf[c].x, qf[c].y);
                mma16816(c0, A0.z, A1.z, A0.w, A1.w, qf[c].z, qf[c].w);
                mma16816(c1, A2.z, A3.z, A2.w, A3.w, qf[c].z, qf[c].w);
            }
            __syncwarp();
            if (lane == 0) mbar_arrive(emptyb + slot * 8);
            const float e0 = (g & 1) ? c0[1] : c0[0], e1 = (g & 1) ? c0[3] : c0[2];
            const float e2 = (g & 1) ? c1[1] : c1[0], e3 = (g & 1) ? c1[3] : c1[2];
            const float sc = ((t & 2) ? ((t & 1) ? e3 : e2) : ((t & 1) ? e1 : e0)) * SCALE_LOG2E;
            ss[i * 32] = sc;
            mx = fmaxf(mx, sc);
            slot += NW / TW;
            if (slot >= NS) { slot -= NS; ph ^= 1; }
        }
#pragma unroll
        for (int o = 16; o; o >>= 1) mx = fmaxf(mx, __shfl_xor_sync(0xffffffffu, mx, o));
        if (lane == 0) misc[w] = mx;
        {
            float ag[2][2][4] = {};
#pragma unroll
            for (int grp = 0; grp < 2; grp++)
#pragma unroll
                for (int mm = 0; mm < 2; mm++) gemv_mma(ag[mm], fg[grp][mm][0], fg[grp][mm][1], bx[grp][0], bx[grp][1]);
            const uint32_t a = sb + SM_RED + w * RED_WSTRIDE + 512 + g * 32 + (t >> 1) * 256 + (t & 1) * 16;
            float v[4];
#pragma unroll
            for (int e = 0; e < 4; e++) v[e] = (t & 2) ? ((t & 1) ? ag[1][1][e] : ag[1][0][e]) : ((t & 1) ? ag[0][1][e] : ag[0][0][e]);
            sts128f_p(a, v, 1);
        }
        bar_sync(1, NW * 32);
        if (tid >= 128) {
            float v = 0.f;
#pragma unroll
            for (int i = 0; i < NW; i++) v += lds32f(sb + SM_RED + i * RED_WSTRIDE + tid * 4);
            st_ll_p(&g_s.x1[cta][tid], v, tag, 1);
        }
        {
            const float4 a = *reinterpret_cast<const float4*>(misc), b = *reinterpret_cast<const float4*>(misc + 4);
            m = fmaxf(fmaxf(fmaxf(a.x, a.y), fmaxf(a.z, a.w)), fmaxf(fmaxf(b.x, b.y), fmaxf(b.z, b.w)));
            __nv_bfloat16* pp = reinterpret_cast<__nv_bfloat16*>(smem + SM_P) + w * (TPW * 32) + 8 * t + g;
            float l = 0.f;
#pragma unroll
            for (int i = 0; i < TPW; i++) {
                const __nv_bfloat16 p = __float2bfloat16_rn(ex2(ss[i * 32] - m));
                pp[i * 32] = p;
                l += __bfloat162float(p);
            }
#pragma unroll
            for (int o = 16; o; o >>= 1) l += __shfl_xor_sync(0xffffffffu, l, o);
            if (lane == 0) misc[8 + w] = l;
            __syncwarp();
        }

        const bool actP = (g >> 1) == t;
        const uint32_t selP0 = actP ? selR0 : 0x4444u;
        const uint32_t selP1 = actP ? selR1 : 0x4444u;
        const uint32_t voff = (8 * t) * 256 + ((g + 2 * t) & 7) * 16;
#pragma unroll 1
        for (int i = 0; i < TPW; i++) {
            if (i == TPW / 2 && w >= 4) reinterpret_cast<float*>(smem + SM_GU)[tid - 128] = bf16r(gather_x1(px, h, tid, tag));
            const uint4 pf = lds128(sb + SM_P + (w * (TPW * 32) + i * 32 + 8 * t) * 2);
            mbar_wait(fullb + slot * 8, ph);
            const uint32_t tb = ring + slot * SLOT_BYTES + voff;
            const uint32_t pw[4] = {pf.x, pf.y, pf.z, pf.w};
#pragma unroll
            for (int grp = 0; grp < 4; grp++) {
                const uint32_t b0 = __byte_perm(pw[grp], 0, selP0), b1 = __byte_perm(pw[grp], 0, selP1);
                const uint32_t a = tb + grp * 512;
                const uint4 A0 = lds128(a), A1 = lds128(a + 256), A2 = lds128(a + 128), A3 = lds128(a + 256 + 128);
                gemv_mma(acc[0], A0, A1, b0, b1);
                gemv_mma(acc[1], A2, A3, b0, b1);
            }
            __syncwarp();
            if (lane == 0) mbar_arrive(emptyb + slot * 8);
            slot += NW / TW;
            if (slot >= NS) { slot -= NS; ph ^= 1; }
        }
    } else {
        if (lane == 0) *reinterpret_cast<volatile int*>(misc + 18) = 0;
        tag += 1;
        uint4 xa = ldg_nc(x + lane * 16), xb = ldg_nc(x + lane * 16 + 8);
        uint4 ga = ldg_nc(gate_w + lane * 16), gb = ldg_nc(gate_w + lane * 16 + 8);
        const uint32_t xr[8] = {xa.x, xa.y, xa.z, xa.w, xb.x, xb.y, xb.z, xb.w};
        const uint32_t gr[8] = {ga.x, ga.y, ga.z, ga.w, gb.x, gb.y, gb.z, gb.w};
        float a = 0.f;
#pragma unroll
        for (int i = 0; i < 8; i++) {
            a += bf16r(__uint_as_float(xr[i] << 16) * __uint_as_float(gr[i] << 16));
            a += bf16r(__uint_as_float(xr[i] & 0xffff0000u) * __uint_as_float(gr[i] & 0xffff0000u));
        }
#pragma unroll
        for (int o = 16; o; o >>= 1) a += __shfl_xor_sync(0xffffffffu, a, o);
        a = bf16r(a);
        const float gate = bf16r(1.f / (1.f + __expf(-a)));
        if (lane == 0) {
            misc[16] = gate;
            misc[17] = bf16r(1.f - gate);
        }
    }

    const int is_aux = opaque(w > NW);
    const int col = tid >> 1, half = tid & 1;
#pragma unroll 1
    for (int pass = is_aux ? 0 : 1; pass < 2; pass++) {
        const int real = opaque(pass);
        const int con = opaque(!is_aux);
        float af[2][4] = {};
        uint4 fo[4][2] = {};
        if (con || !real) {
            const uint32_t a = sb + SM_RED + w * RED_WSTRIDE + t * 512 + (t >> 1) * 16 + ((g + 2 * t) & 7) * 32;
            sts128f_p(a, acc[0][0], con); sts128f_p(a + 16, acc[0][1], con);
            sts128f_p(a + 256, acc[1][0], con); sts128f_p(a + 256 + 16, acc[1][1], con);
            bar_sync_p<1, NW * 32>(con);
            float v = 0.f;
            const uint32_t rp = sb + SM_RED + half * (4 * RED_WSTRIDE) + col * 4;
#pragma unroll
            for (int i = 0; i < 4; i++)
#pragma unroll
                for (int tt = 0; tt < 4; tt++) v += lds32f(rp + i * RED_WSTRIDE + tt * 512 + (tt >> 1) * 16);
            v += __shfl_xor_sync(0xffffffffu, v, 1);
            st_ll_p(&g_s.x2[cta][col], v, tag, con && half == 0);
            {
                const uint4 la = lds128(sb + SM_MISC + 32), lb = lds128(sb + SM_MISC + 48);
                const float l = ((__uint_as_float(la.x) + __uint_as_float(la.y)) + (__uint_as_float(la.z) + __uint_as_float(la.w))) +
                                ((__uint_as_float(lb.x) + __uint_as_float(lb.y)) + (__uint_as_float(lb.z) + __uint_as_float(lb.w)));
                st_ll4_p(&g_s.x2ml[cta][tid & 1], m, l, tag, tid < 2);
            }
            uint32_t hfrag[2];
#pragma unroll
                for (int ci = 0; ci < 2; ci++) {
                const int f = 8 * (s + 4 * ci) + 2 * t;
                const uint2 gg = lds64(sb + SM_GU + f * 4), uu = lds64(sb + SM_GU + 256 + f * 4);
                hfrag[ci] = pack_bf16(__uint_as_float(gg.x) * __uint_as_float(uu.x), __uint_as_float(gg.y) * __uint_as_float(uu.y));
            }
            const uint32_t wa = sb + SM_RING + (w & 7) * 128 + g * 16;
            mbar_wait_p(fullb + (NTT % NS) * 8, (NTT / NS) & 1, con);
            {
                const uint32_t a0 = wa + (NTT % NS) * SLOT_BYTES + t * 2080;
                uint32_t b0 = __byte_perm(hfrag[0], 0, selR0), b1 = __byte_perm(hfrag[0], 0, selR1);
                gemv_mma(af, lds128(a0), lds128(a0 + 1024), b0, b1);
                if (s + 4 < nch) {
                    b0 = __byte_perm(hfrag[1], 0, selR0), b1 = __byte_perm(hfrag[1], 0, selR1);
                    gemv_mma(af, lds128(a0 + 4 * 2080), lds128(a0 + 4 * 2080 + 1024), b0, b1);
                }
            }
#pragma unroll
            for (int k = 0; k < 2; k++) {
                mbar_wait_p(fullb + ((NTT + 1 + k) % NS) * 8, ((NTT + 1 + k) / NS) & 1, con);
                const uint32_t a0 = wa + ((NTT + 1 + k) % NS) * SLOT_BYTES + t * 4128;
                fo[2 * k][0] = lds128(a0);
                fo[2 * k][1] = lds128(a0 + 1024);
                fo[2 * k + 1][0] = lds128(a0 + 2048);
                fo[2 * k + 1][1] = lds128(a0 + 3072);
            }
        }
        uint4 e[8];
        const uint4* src3 = &g_s.x3[cta][lane >> 1][lane & 1];
        if (is_aux) {
            uint2 o4[4];
            uint4 ml[4];
            const uint2* src = &g_s.x2[h * 4][32 * s + lane];
            unsigned n = 0;
            bool ok;
            if (real) {
                while (*reinterpret_cast<volatile int*>(misc + 18) == 0) {
                    {
                        const int own0 = *reinterpret_cast<volatile int*>(misc + 20);
                        unsigned G;
                        asm volatile("ld.relaxed.gpu.global.u32 %0, [%1];" : "=r"(G) : "l"(&g_s.prog) : "memory");
                        G -= (tag - 1) * (unsigned)(NCTA * NTT);
                        const int own1 = *reinterpret_cast<volatile int*>(misc + 20);
                        const int lead = (own0 + own1) * (NCTA / 2) - (int)G;
                        const int win = WIN + (lead > 2 * FB ? -2 : lead > FB ? -1 : lead < -2 * FB ? 2 : lead < -FB ? 1 : 0);
                        if (lane == 0 && own1 >= 8) *reinterpret_cast<volatile int*>(misc + 19) = win;
                    }
                    __nanosleep(200);
                    if (++n > SPIN_LIMIT) __trap();
                }
            }
#pragma unroll
            for (int k = 0; k < 8; k++) {
                e[k] = make_uint4(0, tag, 0, tag);
                ld_ll4_p(e[k], src3 + k * 32, real);
            }
            do {
                ok = true;
#pragma unroll
                for (int i = 0; i < 4; i++) {
                    o4[i] = make_uint2(0, tag);
                    ml[i] = make_uint4(0, tag, 0, tag);
                    ld_ll2_p(o4[i], src + i * 128, real);
                    ld_ll4_p(ml[i], &g_s.x2ml[h * 4 + i][0], real);
                }
#pragma unroll
                for (int i = 0; i < 4; i++) ok = ok && o4[i].y == tag && ml[i].y == tag && ml[i].w == tag;
                if (++n > SPIN_LIMIT) __trap();
            } while (!ok);
            const float M = fmaxf(fmaxf(__uint_as_float(ml[0].x), __uint_as_float(ml[1].x)),
                                  fmaxf(__uint_as_float(ml[2].x), __uint_as_float(ml[3].x)));
            float den = 0.f, num = 0.f;
#pragma unroll
            for (int i = 0; i < 4; i++) {
                const float wt = ex2(__uint_as_float(ml[i].x) - M);
                den += wt * __uint_as_float(ml[i].z);
                num += wt * __uint_as_float(o4[i].x);
            }
            const uint32_t p0 = pack_bf16(__fdividef(num, den), 0.f);
            asm volatile("{\n.reg .pred p;\nsetp.ne.s32 p, %2, 0;\n@p st.shared.u16 [%0], %1;\n}"
                         ::"r"(sb + SM_O + (((lane >> 2) & 3) * 8 + (lane >> 4) * 4 + (lane & 3)) * 2), "h"((unsigned short)p0), "r"(real) : "memory");
        }
        bar_sync_p<2, NW * 32 + 32>(real);
        if (con || !real) {
            const uint4 ow = lds128(sb + SM_O + t * 16);
            const uint2 gt = lds64(sb + SM_MISC + 64);
            const uint32_t oc[4] = {ow.x, ow.y, ow.z, ow.w};
            float a0[2][4] = {}, a1[2][4] = {};
#pragma unroll
            for (int grp = 0; grp < 4; grp++) {
                const uint32_t b0 = __byte_perm(oc[grp], 0, selR0), b1 = __byte_perm(oc[grp], 0, selR1);
                gemv_mma((grp & 1) ? a1 : a0, fo[grp][0], fo[grp][1], b0, b1);
            }
            const float gate = __uint_as_float(gt.x), omg = __uint_as_float(gt.y);
            float r[2][4];
#pragma unroll
            for (int j = 0; j < 2; j++)
#pragma unroll
                for (int q = 0; q < 4; q++) r[j][q] = gate * (a0[j][q] + a1[j][q]) + omg * af[j][q];
            const float v0 = (t & 2) ? ((t & 1) ? r[1][2] : r[1][0]) : ((t & 1) ? r[0][2] : r[0][0]);
            const float v1 = (t & 2) ? ((t & 1) ? r[1][3] : r[1][1]) : ((t & 1) ? r[0][3] : r[0][1]);
            st_ll4_p(&g_s.x3[(16 * w + 2 * g + (t >> 1)) & (NCTA - 1)][cta][t & 1], v0, v1, tag, con);
        }
        if (is_aux) {
            unsigned n = 0;
            bool ok;
            do {
                ok = true;
#pragma unroll
                for (int k = 0; k < 8; k++) ld_ll4_p(e[k], src3 + k * 32, e[k].y != tag || e[k].w != tag);
#pragma unroll
                for (int k = 0; k < 8; k++) ok = ok && e[k].y == tag && e[k].w == tag;
                if (++n > SPIN_LIMIT) __trap();
            } while (!ok);
            float v0 = 0.f, v1 = 0.f;
#pragma unroll
            for (int k = 0; k < 8; k++) { v0 += __uint_as_float(e[k].x); v1 += __uint_as_float(e[k].z); }
            __syncwarp();
#pragma unroll
            for (int o = 16; o > 1; o >>= 1) {
                v0 += __shfl_xor_sync(0xffffffffu, v0, o);
                v1 += __shfl_xor_sync(0xffffffffu, v1, o);
            }
            asm volatile("{\n.reg .pred p;\nsetp.ne.s32 p, %2, 0;\n@p st.global.u32 [%0], %1;\n}"
                         ::"l"(out + cta * 4 + lane * 2), "r"(pack_bf16(v0, v1)), "r"((int)(real && lane < 2)) : "memory");
            asm volatile("{\n.reg .pred p;\nsetp.ne.s32 p, %2, 0;\n@p st.global.u32 [%0], %1;\n}"
                         ::"l"(&g_s.epoch), "r"(tag), "r"((int)(real && lane == 0 && cta == 0)) : "memory");
        }
    }
    }
}

}

extern "C" void kernel_launch(void* const* d_in, const int* in_sizes, int n_in, void* d_out, int out_size) {
    (void)in_sizes; (void)n_in; (void)out_size;
    static bool init = false;
    if (!init) {
        cudaFuncSetAttribute(fused_kernel, cudaFuncAttributeMaxDynamicSharedMemorySize, SM_TOTAL);
        init = true;
    }
    fused_kernel<<<NCTA, NTHREADS, SM_TOTAL>>>(
        (const __nv_bfloat16*)d_in[0], (const __nv_bfloat16*)d_in[1], (const __nv_bfloat16*)d_in[2],
        (const __nv_bfloat16*)d_in[3], (const __nv_bfloat16*)d_in[4], (const __nv_bfloat16*)d_in[6],
        (const __nv_bfloat16*)d_in[7], (const __nv_bfloat16*)d_in[8], (const __nv_bfloat16*)d_in[9],
        (__nv_bfloat16*)d_out);
}
```

```cpp
#include <cuda_runtime.h>
#include <cuda_bf16.h>
#include <stdint.h>

namespace {

constexpr int D_MODEL = 512;
constexpr int NH = 32;
constexpr int SK = 8192;
constexpr int DH = 128;
constexpr int FF = 1376;
constexpr int NSPLIT = 4;
constexpr int NCTA = NH * NSPLIT;
constexpr int KEYS_CTA = SK / NSPLIT;
constexpr int NW = 8;
constexpr int WT_BYTES = 32 * DH * 2;
constexpr int TW = 2;
constexpr int NS = 12;
constexpr int WIN = 4;
constexpr int FB = 160;
constexpr int FLAG_AT = 2;
constexpr int TT_BYTES = TW * WT_BYTES;
constexpr int SLOT_BYTES = TT_BYTES + 256;
constexpr int TPW = KEYS_CTA / 32 / NW;
constexpr int NTT = 2 * TPW * NW / TW;
constexpr int NTHREADS = NW * 32 + 64;

constexpr int SM_RING = 0;
constexpr int SM_RED = SM_RING + NS * SLOT_BYTES;
constexpr int RED_WSTRIDE = 2096;
constexpr int SM_SS = SM_RED;
constexpr int SM_P = SM_RED + NW * RED_WSTRIDE;
constexpr int SM_Q = SM_P + NW * TPW * 32 * 2;
constexpr int SM_O = SM_Q + 256;
constexpr int SM_GU = SM_O + 64;
constexpr int SM_MISC = SM_GU + 512;
constexpr int SM_BAR = SM_MISC + 128;
constexpr int SM_TOTAL = SM_BAR + 2 * NS * 8 + 512;
static_assert(SM_TOTAL <= 232448, "smem");

struct Scratch {
    uint2 x1[NCTA][256];
    uint2 x2[NCTA][128];
    uint4 x2ml[NCTA][2];
    uint4 x3[NCTA][NCTA][2];
    unsigned epoch;
    unsigned pad[31];
    unsigned prog;
};
__device__ Scratch g_s;

__device__ __forceinline__ uint32_t s2u(const void* p) { return (uint32_t)__cvta_generic_to_shared(p); }
__device__ __forceinline__ void mbar_init(uint32_t a, int c) {
    asm volatile("mbarrier.init.shared::cta.b64 [%0], %1;" ::"r"(a), "r"(c) : "memory");
}
__device__ __forceinline__ void mbar_expect(uint32_t a, uint32_t b) {
    asm volatile("mbarrier.arrive.expect_tx.shared::cta.b64 _, [%0], %1;" ::"r"(a), "r"(b) : "memory");
}
__device__ __forceinline__ void mbar_arrive(uint32_t a) {
    asm volatile("mbarrier.arrive.shared::cta.b64 _, [%0];" ::"r"(a) : "memory");
}
__device__ __forceinline__ void mbar_wait(uint32_t a, uint32_t ph) {
    uint32_t ok, n = 0;
    do {
        asm volatile("{\n.reg .pred p;\nmbarrier.try_wait.parity.shared::cta.b64 p, [%1], %2;\nselp.u32 %0, 1, 0, p;\n}"
                     : "=r"(ok) : "r"(a), "r"(ph) : "memory");
        if (++n > (1u << 22)) __trap();
    } while (!ok);
}
__device__ __forceinline__ uint32_t mbar_try(uint32_t a, uint32_t ph) {
    uint32_t ok;
    asm volatile("{\n.reg .pred p;\nmbarrier.try_wait.parity.shared::cta.b64 p, [%1], %2, 200;\nselp.u32 %0, 1, 0, p;\n}"
                 : "=r"(ok) : "r"(a), "r"(ph) : "memory");
    return ok;
}
__device__ __forceinline__ void mbar_wait_p(uint32_t a, uint32_t ph, int en) {
    uint32_t ok, n = 0;
    do {
        asm volatile("{\n.reg .pred p, q;\nsetp.eq.s32 p, %3, 0;\nsetp.ne.s32 q, %3, 0;\n@q mbarrier.try_wait.parity.shared::cta.b64 p, [%1], %2;\nselp.u32 %0, 1, 0, p;\n}"
                     : "=r"(ok) : "r"(a), "r"(ph), "r"(en) : "memory");
        if (++n > (1u << 22)) __trap();
    } while (!ok);
}
__device__ __forceinline__ void bulk_ld(uint32_t dst, const void* src, uint32_t bytes, uint32_t bar) {
    uint64_t pol;
    asm volatile("createpolicy.fractional.L2::evict_first.b64 %0, 1.0;" : "=l"(pol));
    asm volatile("cp.async.bulk.shared::cluster.global.mbarrier::complete_tx::bytes.L2::cache_hint [%0], [%1], %2, [%3], %4;"
                 ::"r"(dst), "l"(src), "r"(bytes), "r"(bar), "l"(pol) : "memory");
}
__device__ __forceinline__ uint4 ldg_nc(const void* p) {
    uint4 v;
    asm volatile("ld.global.nc.L1::no_allocate.v4.u32 {%0,%1,%2,%3}, [%4];"
                 : "=r"(v.x), "=r"(v.y), "=r"(v.z), "=r"(v.w) : "l"(p));
    return v;
}
__device__ __forceinline__ void ldg_nc_p(uint4& v, const void* a, int p) {
    uint64_t pol;
    asm volatile("createpolicy.fractional.L2::evict_first.b64 %0, 1.0;" : "=l"(pol));
    asm volatile("{\n.reg .pred p;\nsetp.ne.s32 p, %5, 0;\n@p ld.global.nc.L1::no_allocate.L2::cache_hint.v4.u32 {%0,%1,%2,%3}, [%4], %6;\n}"
                 : "+r"(v.x), "+r"(v.y), "+r"(v.z), "+r"(v.w) : "l"(a), "r"(p), "l"(pol));
}
__device__ __forceinline__ uint4 lds128(uint32_t a) {
    uint4 v;
    asm volatile("ld.shared.v4.u32 {%0,%1,%2,%3}, [%4];" : "=r"(v.x), "=r"(v.y), "=r"(v.z), "=r"(v.w) : "r"(a));
    return v;
}
__device__ __forceinline__ uint2 lds64(uint32_t a) {
    uint2 v;
    asm volatile("ld.shared.v2.u32 {%0,%1}, [%2];" : "=r"(v.x), "=r"(v.y) : "r"(a));
    return v;
}
__device__ __forceinline__ float lds32f(uint32_t a) {
    float v;
    asm volatile("ld.shared.f32 %0, [%1];" : "=f"(v) : "r"(a));
    return v;
}
__device__ __forceinline__ void sts128f_p(uint32_t a, const float (&c)[4], int p) {
    asm volatile("{\n.reg .pred p;\nsetp.ne.s32 p, %5, 0;\n@p st.shared.v4.f32 [%0], {%1,%2,%3,%4};\n}"
                 ::"r"(a), "f"(c[0]), "f"(c[1]), "f"(c[2]), "f"(c[3]), "r"(p) : "memory");
}
__device__ __forceinline__ void ld_ll2_p(uint2& v, const void* a, int p) {
    asm volatile("{\n.reg .pred p;\nsetp.ne.s32 p, %3, 0;\n@p ld.relaxed.gpu.global.v2.u32 {%0,%1}, [%2];\n}"
                 : "+r"(v.x), "+r"(v.y) : "l"(a), "r"(p) : "memory");
}
__device__ __forceinline__ void ld_ll4_p(uint4& v, const void* a, int p) {
    asm volatile("{\n.reg .pred p;\nsetp.ne.s32 p, %5, 0;\n@p ld.relaxed.gpu.global.v4.u32 {%0,%1,%2,%3}, [%4];\n}"
                 : "+r"(v.x), "+r"(v.y), "+r"(v.z), "+r"(v.w) : "l"(a), "r"(p) : "memory");
}
__device__ __forceinline__ void st_ll_p(uint2* a, float v, unsigned tag, int p) {
    asm volatile("{\n.reg .pred p;\nsetp.ne.s32 p, %3, 0;\n@p st.relaxed.gpu.global.v2.u32 [%0], {%1,%2};\n}"
                 ::"l"(a), "r"(__float_as_uint(v)), "r"(tag), "r"(p) : "memory");
}
__device__ __forceinline__ void st_ll4_p(void* a, float v0, float v1, unsigned tag, int p) {
    asm volatile("{\n.reg .pred p;\nsetp.ne.s32 p, %4, 0;\n@p st.relaxed.gpu.global.v4.u32 [%0], {%1,%2,%3,%2};\n}"
                 ::"l"(a), "r"(__float_as_uint(v0)), "r"(tag), "r"(__float_as_uint(v1)), "r"(p) : "memory");
}
__device__ __forceinline__ void mma16816(float (&c)[4], uint32_t a0, uint32_t a1, uint32_t a2, uint32_t a3,
                                         uint32_t b0, uint32_t b1) {
    asm volatile("mma.sync.aligned.m16n8k16.row.col.f32.bf16.bf16.f32 {%0,%1,%2,%3}, {%4,%5,%6,%7}, {%8,%9}, {%0,%1,%2,%3};"
                 : "+f"(c[0]), "+f"(c[1]), "+f"(c[2]), "+f"(c[3])
                 : "r"(a0), "r"(a1), "r"(a2), "r"(a3), "r"(b0), "r"(b1));
}
__device__ __forceinline__ void gemv_mma(float (&acc)[2][4], const uint4& L0, const uint4& L1, uint32_t b0, uint32_t b1) {
    mma16816(acc[0], L0.x, L0.y, L1.x, L1.y, b0, b1);
    mma16816(acc[1], L0.z, L0.w, L1.z, L1.w, b0, b1);
}
__device__ __forceinline__ float ex2(float x) {
    float y; asm("ex2.approx.ftz.f32 %0, %1;" : "=f"(y) : "f"(x)); return y;
}
__device__ __forceinline__ float bf16r(float x) { return __bfloat162float(__float2bfloat16_rn(x)); }
__device__ __forceinline__ uint32_t pack_bf16(float lo, float hi) {
    uint32_t r; asm("cvt.rn.bf16x2.f32 %0, %1, %2;" : "=r"(r) : "f"(hi), "f"(lo)); return r;
}
__device__ __forceinline__ void bar_sync(int id, int n) { asm volatile("bar.sync %0, %1;" ::"r"(id), "r"(n) : "memory"); }
template <int ID, int N>
__device__ __forceinline__ void bar_sync_p(int p) {
    asm volatile("{\n.reg .pred p;\nsetp.ne.s32 p, %0, 0;\n@p bar.sync %1, %2;\n}" ::"r"(p), "n"(ID), "n"(N) : "memory");
}
__device__ __forceinline__ int opaque(int v) { asm volatile("" : "+r"(v)); return v; }

constexpr unsigned SPIN_LIMIT = 1u << 24;

__device__ __forceinline__ float gather_x1(uint2 (&p)[4], int h, int idx, unsigned tag) {
    unsigned n = 0;
    bool ok;
    do {
        ok = true;
#pragma unroll
        for (int i = 0; i < 4; i++) ld_ll2_p(p[i], &g_s.x1[h * 4 + i][idx], p[i].y != tag);
#pragma unroll
        for (int i = 0; i < 4; i++) ok = ok && p[i].y == tag;
        if (!ok) __nanosleep(100);
        if (++n > SPIN_LIMIT) __trap();
    } while (!ok);
    return (__uint_as_float(p[0].x) + __uint_as_float(p[1].x)) + (__uint_as_float(p[2].x) + __uint_as_float(p[3].x));
}

__global__ void __launch_bounds__(NTHREADS, 1)
fused_kernel(const __nv_bfloat16* __restrict__ x, const __nv_bfloat16* __restrict__ kc,
             const __nv_bfloat16* __restrict__ vc, const __nv_bfloat16* __restrict__ wq,
             const __nv_bfloat16* __restrict__ wo, const __nv_bfloat16* __restrict__ wg,
             const __nv_bfloat16* __restrict__ wu, const __nv_bfloat16* __restrict__ wd,
             const __nv_bfloat16* __restrict__ gate_w, __nv_bfloat16* __restrict__ out) {
    extern __shared__ __align__(1024) unsigned char smem[];
    const uint32_t sb = s2u(smem);
    const int tid = threadIdx.x, lane = tid & 31;
    const int w = __shfl_sync(0xffffffffu, tid >> 5, 0);
    const int g = lane >> 2, t = lane & 3;
    const int cta = blockIdx.x, h = cta >> 2, s = cta & 3;
    float* misc = reinterpret_cast<float*>(smem + SM_MISC);
    const uint32_t fullb = sb + SM_BAR, emptyb = sb + SM_BAR + NS * 8;
    const int nch = h < 12 ? 6 : 5;
    const int ch0 = h < 12 ? 6 * h : 72 + 5 * (h - 12);

    const size_t kvoff = ((size_t)h * SK + (size_t)s * KEYS_CTA) * (DH * 2);
    if (__builtin_expect(tid == NW * 32, 1)) {
#pragma unroll
        for (int i = 0; i < WIN; i++) mbar_init(fullb + i * 8, 1);
        asm volatile("fence.mbarrier_init.release.cluster;" ::: "memory");
#pragma unroll
        for (int i = 0; i < WIN; i++) {
            mbar_expect(fullb + i * 8, TT_BYTES);
            bulk_ld(sb + SM_RING + i * SLOT_BYTES, reinterpret_cast<const unsigned char*>(kc) + kvoff + i * TT_BYTES, TT_BYTES, fullb + i * 8);
        }
    }
    const int r0 = 128 * s + 16 * w + 4 * t;
    uint4 fq[2][2][2] = {};
    uint2 xw = make_uint2(0, 0);
    uint2 px[4] = {};
    unsigned tag;
    {
        const __nv_bfloat16* p = wq + (size_t)r0 * (NH * DH) + h * DH + g * 8;
        const int con = w < NW;
#pragma unroll
        for (int grp = 0; grp < 2; grp++)
#pragma unroll
            for (int r = 0; r < 2; r++)
#pragma unroll
                for (int win = 0; win < 2; win++)
                    ldg_nc_p(fq[grp][win][r], p + (size_t)(2 * grp + r) * (NH * DH) + win * 64, con);
        asm volatile("{\n.reg .pred p;\nsetp.ne.s32 p, %3, 0;\n@p ld.global.nc.v2.u32 {%0,%1}, [%2];\n}"
                     : "+r"(xw.x), "+r"(xw.y) : "l"(x + r0), "r"(con));
        asm volatile("ld.relaxed.gpu.global.u32 %0, [%1];" : "=r"(tag) : "l"(&g_s.epoch) : "memory");
    }
    if (__builtin_expect(w == NW, 1)) {
        if (lane == 0) {
#pragma unroll
            for (int i = WIN; i < NS; i++) mbar_init(fullb + i * 8, 1);
#pragma unroll
            for (int i = 0; i < NS; i++) mbar_init(emptyb + i * 8, TW);
            *reinterpret_cast<volatile int*>(misc + 19) = WIN;
            *reinterpret_cast<volatile int*>(misc + 20) = 0;
            asm volatile("fence.mbarrier_init.release.cluster;" ::: "memory");
        }
        __syncwarp();
        asm volatile("bar.arrive 3, %0;" ::"n"(NW * 32 + 32) : "memory");
        const unsigned char* src = reinterpret_cast<const unsigned char*>(kc) + kvoff + WIN * TT_BYTES;
        int slot = WIN, lslot = 0, landed = 0;
        uint32_t eph = 1, lph = 0, spins = 0;
#pragma unroll 1
        for (int j = WIN; j < NTT + 3; j++) {
            if (j == NTT / 2) src = reinterpret_cast<const unsigned char*>(vc) + kvoff;
            mbar_wait(emptyb + slot * 8, eph);
            while (landed < min(NTT, (j < NTT ? j : NTT) + 1 - *reinterpret_cast<volatile int*>(misc + 19))) {
                if (!mbar_try(fullb + lslot * 8, lph)) { if (++spins > (1u << 24)) __trap(); continue; }
                landed++;
                if (lane == 0) {
                    asm volatile("red.relaxed.gpu.global.add.u32 [%0], 1;" ::"l"(&g_s.prog) : "memory");
                    *reinterpret_cast<volatile int*>(misc + 20) = landed;
                }
                if (++lslot == NS) { lslot = 0; lph ^= 1; }
            }
            int n = 1, bytes = TT_BYTES;
            if (j >= NTT) {
                n = (j > NTT || s + 4 >= nch) ? 4 : 8;
                bytes = j > NTT ? 4096 : 2048;
                src = j > NTT ? reinterpret_cast<const unsigned char*>(wo + (size_t)(h * DH + 32 * s + (j - NTT - 1) * 16) * D_MODEL)
                              : reinterpret_cast<const unsigned char*>(wd + (size_t)(8 * (ch0 + s)) * D_MODEL);
            }
            if (lane == 0) {
                uint32_t dst = sb + SM_RING + slot * SLOT_BYTES;
                const uint32_t bar = fullb + slot * 8;
                mbar_expect(bar, n * bytes);
#pragma unroll 1
                for (int i = 0; i < n; i++) {
                    bulk_ld(dst, src + i * bytes + (i >= 4 ? 24576 : 0), bytes, bar);
                    dst += bytes + 32;
                }
                if (j == NTT - FLAG_AT) *reinterpret_cast<volatile int*>(misc + 18) = 1;
            }
            src += TT_BYTES;
            if (++slot == NS) { slot = 0; eph ^= 1; }
        }
    }
    if (opaque(w) == NW) return;

    const uint32_t selR0 = (g & 1) ? 0x1044u : 0x4410u;
    const uint32_t selR1 = (g & 1) ? 0x3244u : 0x4432u;

    float acc[2][2][4] = {};
    float m = 0.f;

    if (__builtin_expect(w < NW, 1)) {
        uint4 fg[2][2][2] = {};
        st_ll_p(&g_s.x1[cta][tid], 0.f, 0, 1);
        st_ll_p(&g_s.x2[cta][tid >> 1], 0.f, 0, !(tid & 1));
        st_ll4_p(&g_s.x2ml[cta][tid & 1], 0.f, 0.f, 0, tid < 2);
        st_ll4_p(&g_s.x3[16 * w + 2 * g + (t >> 1)][cta][t & 1], 0.f, 0.f, 0, 1);
        uint32_t bx[2][2];
        {
            float aq[2][2][4] = {};
#pragma unroll
            for (int grp = 0; grp < 2; grp++) {
                const uint32_t c = grp ? xw.y : xw.x;
                bx[grp][0] = __byte_perm(c, 0, selR0); bx[grp][1] = __byte_perm(c, 0, selR1);
#pragma unroll
                for (int win = 0; win < 2; win++) gemv_mma(aq[win], fq[grp][win][0], fq[grp][win][1], bx[grp][0], bx[grp][1]);
            }
            const uint32_t a = sb + SM_RED + w * RED_WSTRIDE + g * 32 + (t >> 1) * 256 + (t & 1) * 16;
            float v[4];
#pragma unroll
            for (int e = 0; e < 4; e++) v[e] = (t & 2) ? ((t & 1) ? aq[1][1][e] : aq[1][0][e]) : ((t & 1) ? aq[0][1][e] : aq[0][0][e]);
            sts128f_p(a, v, 1);
        }
        {
            const size_t off = (size_t)r0 * FF + (ch0 + g) * 8;
            const int ok = g < nch;
#pragma unroll
            for (int grp = 0; grp < 2; grp++)
#pragma unroll
                for (int r = 0; r < 2; r++) {
                    ldg_nc_p(fg[grp][0][r], wg + off + (size_t)(2 * grp + r) * FF, ok);
                    ldg_nc_p(fg[grp][1][r], wu + off + (size_t)(2 * grp + r) * FF, ok);
                }
        }
        tag += 1;
        bar_sync(1, NW * 32);
        if (tid < 128) {
            float v = 0.f;
#pragma unroll
            for (int i = 0; i < NW; i++) v += lds32f(sb + SM_RED + i * RED_WSTRIDE + tid * 4);
            st_ll_p(&g_s.x1[cta][tid], v, tag, 1);
            v = gather_x1(px, h, tid, tag);
            reinterpret_cast<__nv_bfloat16*>(smem + SM_Q)[tid] = __float2bfloat16_rn(v);
        }
        bar_sync(3, NW * 32 + 32);
        if (tid == 0) *reinterpret_cast<volatile int*>(misc + 19) = WIN;

        uint4 qf[4];
#pragma unroll
        for (int c = 0; c < 4; c++) qf[c] = lds128(sb + SM_Q + (t + 4 * (c ^ (g & 1))) * 16);
        float mx = -INFINITY;
        float* ss = reinterpret_cast<float*>(smem + SM_SS + w * RED_WSTRIDE + 1024) + lane;
        int slot = w / TW;
        uint32_t ph = 0;
        const uint32_t ring = sb + SM_RING + (w % TW) * WT_BYTES;
#pragma unroll 1
        for (int i = 0; i < TPW; i++) {
            mbar_wait(fullb + slot * 8, ph);
            const uint32_t tb = ring + slot * SLOT_BYTES + g * 256;
            float c0[4] = {}, c1[4] = {};
#pragma unroll
            for (int c = 0; c < 4; c++) {
                const uint32_t a = tb + (t + 4 * (c ^ (g & 1))) * 16;
                const uint4 A0 = lds128(a), A1 = lds128(a + 8 * 256), A2 = lds128(a + 16 * 256), A3 = lds128(a + 24 * 256);
                mma16816(c0, A0.x, A1.x, A0.y, A1.y, qf[c].x, qf[c].y);
                mma16816(c1, A2.x, A3.x, A2.y, A3.y, qf[c].x, qf[c].y);
                mma16816(c0, A0.z, A1.z, A0.w, A1.w, qf[c].z, qf[c].w);
                mma16816(c1, A2.z, A3.z, A2.w, A3.w, qf[c].z, qf[c].w);
            }
            __syncwarp();
            if (lane == 0) mbar_arrive(emptyb + slot * 8);
            const float e0 = (g & 1) ? c0[1] : c0[0], e1 = (g & 1) ? c0[3] : c0[2];
            const float e2 = (g & 1) ? c1[1] : c1[0], e3 = (g & 1) ? c1[3] : c1[2];
            const float sc = bf16r(bf16r((t & 2) ? ((t & 1) ? e3 : e2) : ((t & 1) ? e1 : e0)) * 0.08838834764831845f) * 1.4426950408889634f;
            ss[i * 32] = sc;
            mx = fmaxf(mx, sc);
            slot += NW / TW;
            if (slot >= NS) { slot -= NS; ph ^= 1; }
        }
#pragma unroll
        for (int o = 16; o; o >>= 1) mx = fmaxf(mx, __shfl_xor_sync(0xffffffffu, mx, o));
        if (lane == 0) misc[w] = mx;
        {
            float ag[2][2][4] = {};
#pragma unroll
            for (int grp = 0; grp < 2; grp++)
#pragma unroll
                for (int mm = 0; mm < 2; mm++) gemv_mma(ag[mm], fg[grp][mm][0], fg[grp][mm][1], bx[grp][0], bx[grp][1]);
            const uint32_t a = sb + SM_RED + w * RED_WSTRIDE + 512 + g * 32 + (t >> 1) * 256 + (t & 1) * 16;
            float v[4];
#pragma unroll
            for (int e = 0; e < 4; e++) v[e] = (t & 2) ? ((t & 1) ? ag[1][1][e] : ag[1][0][e]) : ((t & 1) ? ag[0][1][e] : ag[0][0][e]);
            sts128f_p(a, v, 1);
        }
        bar_sync(1, NW * 32);
        if (tid >= 128) {
            float v = 0.f;
#pragma unroll
            for (int i = 0; i < NW; i++) v += lds32f(sb + SM_RED + i * RED_WSTRIDE + tid * 4);
            st_ll_p(&g_s.x1[cta][tid], v, tag, 1);
        }
        {
            const float4 a = *reinterpret_cast<const float4*>(misc), b = *reinterpret_cast<const float4*>(misc + 4);
            m = fmaxf(fmaxf(fmaxf(a.x, a.y), fmaxf(a.z, a.w)), fmaxf(fmaxf(b.x, b.y), fmaxf(b.z, b.w)));
            __nv_bfloat16* pp = reinterpret_cast<__nv_bfloat16*>(smem + SM_P) + w * (TPW * 32) + 8 * t + g;
            float l = 0.f;
#pragma unroll
            for (int i = 0; i < TPW; i++) {
                const __nv_bfloat16 p = __float2bfloat16_rn(ex2(ss[i * 32] - m));
                pp[i * 32] = p;
                l += __bfloat162float(p);
            }
#pragma unroll
            for (int o = 16; o; o >>= 1) l += __shfl_xor_sync(0xffffffffu, l, o);
            if (lane == 0) misc[8 + w] = l;
            __syncwarp();
        }

        const bool actP = (g >> 1) == t;
        const uint32_t selP0 = actP ? selR0 : 0x4444u;
        const uint32_t selP1 = actP ? selR1 : 0x4444u;
        const uint32_t voff = (8 * t) * 256 + ((g + 2 * t) & 7) * 16;
#pragma unroll 1
        for (int i = 0; i < TPW; i++) {
            if (i == TPW / 2 && w >= 4) reinterpret_cast<float*>(smem + SM_GU)[tid - 128] = bf16r(gather_x1(px, h, tid, tag));
            const uint4 pf = lds128(sb + SM_P + (w * (TPW * 32) + i * 32 + 8 * t) * 2);
            mbar_wait(fullb + slot * 8, ph);
            const uint32_t tb = ring + slot * SLOT_BYTES + voff;
            const uint32_t pw[4] = {pf.x, pf.y, pf.z, pf.w};
#pragma unroll
            for (int grp = 0; grp < 4; grp++) {
                const uint32_t b0 = __byte_perm(pw[grp], 0, selP0), b1 = __byte_perm(pw[grp], 0, selP1);
                const uint32_t a = tb + grp * 512;
                const uint4 A0 = lds128(a), A1 = lds128(a + 256), A2 = lds128(a + 128), A3 = lds128(a + 256 + 128);
                gemv_mma(acc[0], A0, A1, b0, b1);
                gemv_mma(acc[1], A2, A3, b0, b1);
            }
            __syncwarp();
            if (lane == 0) mbar_arrive(emptyb + slot * 8);
            slot += NW / TW;
            if (slot >= NS) { slot -= NS; ph ^= 1; }
        }
    } else {
        if (lane == 0) *reinterpret_cast<volatile int*>(misc + 18) = 0;
        tag += 1;
        uint4 xa = ldg_nc(x + lane * 16), xb = ldg_nc(x + lane * 16 + 8);
        uint4 ga = ldg_nc(gate_w + lane * 16), gb = ldg_nc(gate_w + lane * 16 + 8);
        const uint32_t xr[8] = {xa.x, xa.y, xa.z, xa.w, xb.x, xb.y, xb.z, xb.w};
        const uint32_t gr[8] = {ga.x, ga.y, ga.z, ga.w, gb.x, gb.y, gb.z, gb.w};
        float a = 0.f;
#pragma unroll
        for (int i = 0; i < 8; i++) {
            a += bf16r(__uint_as_float(xr[i] << 16) * __uint_as_float(gr[i] << 16));
            a += bf16r(__uint_as_float(xr[i] & 0xffff0000u) * __uint_as_float(gr[i] & 0xffff0000u));
        }
#pragma unroll
        for (int o = 16; o; o >>= 1) a += __shfl_xor_sync(0xffffffffu, a, o);
        a = bf16r(a);
        const float gate = bf16r(1.f / (1.f + __expf(-a)));
        if (lane == 0) {
            misc[16] = gate;
            misc[17] = bf16r(1.f - gate);
        }
    }

    const int is_aux = opaque(w > NW);
    const int col = tid >> 1, half = tid & 1;
#pragma unroll 1
    for (int pass = is_aux ? 0 : 1; pass < 2; pass++) {
        const int real = opaque(pass);
        const int con = opaque(!is_aux);
        float af[2][4] = {};
        uint4 fo[4][2] = {};
        if (con || !real) {
            const uint32_t a = sb + SM_RED + w * RED_WSTRIDE + t * 512 + (t >> 1) * 16 + ((g + 2 * t) & 7) * 32;
            sts128f_p(a, acc[0][0], con); sts128f_p(a + 16, acc[0][1], con);
            sts128f_p(a + 256, acc[1][0], con); sts128f_p(a + 256 + 16, acc[1][1], con);
            bar_sync_p<1, NW * 32>(con);
            float v = 0.f;
            const uint32_t rp = sb + SM_RED + half * (4 * RED_WSTRIDE) + col * 4;
#pragma unroll
            for (int i = 0; i < 4; i++)
#pragma unroll
                for (int tt = 0; tt < 4; tt++) v += lds32f(rp + i * RED_WSTRIDE + tt * 512 + (tt >> 1) * 16);
            v += __shfl_xor_sync(0xffffffffu, v, 1);
            st_ll_p(&g_s.x2[cta][col], v, tag, con && half == 0);
            {
                const uint4 la = lds128(sb + SM_MISC + 32), lb = lds128(sb + SM_MISC + 48);
                const float l = ((__uint_as_float(la.x) + __uint_as_float(la.y)) + (__uint_as_float(la.z) + __uint_as_float(la.w))) +
                                ((__uint_as_float(lb.x) + __uint_as_float(lb.y)) + (__uint_as_float(lb.z) + __uint_as_float(lb.w)));
                st_ll4_p(&g_s.x2ml[cta][tid & 1], m, l, tag, tid < 2);
            }
            uint32_t hfrag[2];
#pragma unroll
            for (int ci = 0; ci < 2; ci++) {
                const int f = 8 * (s + 4 * ci) + 2 * t;
                const uint2 gg = lds64(sb + SM_GU + f * 4), uu = lds64(sb + SM_GU + 256 + f * 4);
                hfrag[ci] = pack_bf16(__uint_as_float(gg.x) * __uint_as_float(uu.x), __uint_as_float(gg.y) * __uint_as_float(uu.y));
            }
            const uint32_t wa = sb + SM_RING + (w & 7) * 128 + g * 16;
            mbar_wait_p(fullb + (NTT % NS) * 8, (NTT / NS) & 1, con);
            {
                const uint32_t a0 = wa + (NTT % NS) * SLOT_BYTES + t * 2080;
                uint32_t b0 = __byte_perm(hfrag[0], 0, selR0), b1 = __byte_perm(hfrag[0], 0, selR1);
                gemv_mma(af, lds128(a0), lds128(a0 + 1024), b0, b1);
                if (s + 4 < nch) {
                    b0 = __byte_perm(hfrag[1], 0, selR0), b1 = __byte_perm(hfrag[1], 0, selR1);
                    gemv_mma(af, lds128(a0 + 4 * 2080), lds128(a0 + 4 * 2080 + 1024), b0, b1);
                }
            }
#pragma unroll
            for (int k = 0; k < 2; k++) {
                mbar_wait_p(fullb + ((NTT + 1 + k) % NS) * 8, ((NTT + 1 + k) / NS) & 1, con);
                const uint32_t a0 = wa + ((NTT + 1 + k) % NS) * SLOT_BYTES + t * 4128;
                fo[2 * k][0] = lds128(a0);
                fo[2 * k][1] = lds128(a0 + 1024);
                fo[2 * k + 1][0] = lds128(a0 + 2048);
                fo[2 * k + 1][1] = lds128(a0 + 3072);
            }
        }
        uint4 e[8];
        const uint4* src3 = &g_s.x3[cta][lane >> 1][lane & 1];
        if (is_aux) {
            uint2 o4[4];
            uint4 ml[4];
            const uint2* src = &g_s.x2[h * 4][32 * s + lane];
            unsigned n = 0;
            bool ok;
            if (real) {
                while (*reinterpret_cast<volatile int*>(misc + 18) == 0) {
                    {
                        const int own0 = *reinterpret_cast<volatile int*>(misc + 20);
                        unsigned G;
                        asm volatile("ld.relaxed.gpu.global.u32 %0, [%1];" : "=r"(G) : "l"(&g_s.prog) : "memory");
                        const int own1 = *reinterpret_cast<volatile int*>(misc + 20);
                        const int lead = (own0 + own1) * (NCTA / 2) - (int)G;
                        const int win = WIN + (lead > 2 * FB ? -2 : lead > FB ? -1 : lead < -2 * FB ? 2 : lead < -FB ? 1 : 0);
                        if (lane == 0 && own1 >= 8) *reinterpret_cast<volatile int*>(misc + 19) = win;
                    }
                    __nanosleep(200);
                    if (++n > SPIN_LIMIT) __trap();
                }
            }
#pragma unroll
            for (int k = 0; k < 8; k++) {
                e[k] = make_uint4(0, tag, 0, tag);
                ld_ll4_p(e[k], src3 + k * 32, real);
            }
            do {
                ok = true;
#pragma unroll
                for (int i = 0; i < 4; i++) {
                    o4[i] = make_uint2(0, tag);
                    ml[i] = make_uint4(0, tag, 0, tag);
                    ld_ll2_p(o4[i], src + i * 128, real);
                    ld_ll4_p(ml[i], &g_s.x2ml[h * 4 + i][0], real);
                }
#pragma unroll
                for (int i = 0; i < 4; i++) ok = ok && o4[i].y == tag && ml[i].y == tag && ml[i].w == tag;
                if (++n > SPIN_LIMIT) __trap();
            } while (!ok);
            const float M = fmaxf(fmaxf(__uint_as_float(ml[0].x), __uint_as_float(ml[1].x)),
                                  fmaxf(__uint_as_float(ml[2].x), __uint_as_float(ml[3].x)));
            float den = 0.f, num = 0.f;
#pragma unroll
            for (int i = 0; i < 4; i++) {
                const float wt = ex2(__uint_as_float(ml[i].x) - M);
                den += wt * __uint_as_float(ml[i].z);
                num += wt * __uint_as_float(o4[i].x);
            }
            const uint32_t p0 = pack_bf16(__fdividef(num, den), 0.f);
            asm volatile("{\n.reg .pred p;\nsetp.ne.s32 p, %2, 0;\n@p st.shared.u16 [%0], %1;\n}"
                         ::"r"(sb + SM_O + (((lane >> 2) & 3) * 8 + (lane >> 4) * 4 + (lane & 3)) * 2), "h"((unsigned short)p0), "r"(real) : "memory");
        }
        bar_sync_p<2, NW * 32 + 32>(real);
        if (con || !real) {
            const uint4 ow = lds128(sb + SM_O + t * 16);
            const uint2 gt = lds64(sb + SM_MISC + 64);
            const uint32_t oc[4] = {ow.x, ow.y, ow.z, ow.w};
            float a0[2][4] = {}, a1[2][4] = {};
#pragma unroll
            for (int grp = 0; grp < 4; grp++) {
                const uint32_t b0 = __byte_perm(oc[grp], 0, selR0), b1 = __byte_perm(oc[grp], 0, selR1);
                gemv_mma((grp & 1) ? a1 : a0, fo[grp][0], fo[grp][1], b0, b1);
            }
            const float gate = __uint_as_float(gt.x), omg = __uint_as_float(gt.y);
            float r[2][4];
#pragma unroll
            for (int j = 0; j < 2; j++)
#pragma unroll
                for (int q = 0; q < 4; q++) r[j][q] = gate * (a0[j][q] + a1[j][q]) + omg * af[j][q];
            const float v0 = (t & 2) ? ((t & 1) ? r[1][2] : r[1][0]) : ((t & 1) ? r[0][2] : r[0][0]);
            const float v1 = (t & 2) ? ((t & 1) ? r[1][3] : r[1][1]) : ((t & 1) ? r[0][3] : r[0][1]);
            st_ll4_p(&g_s.x3[(16 * w + 2 * g + (t >> 1)) & (NCTA - 1)][cta][t & 1], v0, v1, tag, con);
        }
        if (is_aux) {
            unsigned n = 0;
            bool ok;
            do {
                ok = true;
#pragma unroll
                for (int k = 0; k < 8; k++) ld_ll4_p(e[k], src3 + k * 32, e[k].y != tag || e[k].w != tag);
#pragma unroll
                for (int k = 0; k < 8; k++) ok = ok && e[k].y == tag && e[k].w == tag;
                if (++n > SPIN_LIMIT) __trap();
            } while (!ok);
            float v0 = 0.f, v1 = 0.f;
#pragma unroll
            for (int k = 0; k < 8; k++) { v0 += __uint_as_float(e[k].x); v1 += __uint_as_float(e[k].z); }
            __syncwarp();
#pragma unroll
            for (int o = 16; o > 1; o >>= 1) {
                v0 += __shfl_xor_sync(0xffffffffu, v0, o);
                v1 += __shfl_xor_sync(0xffffffffu, v1, o);
            }
            asm volatile("{\n.reg .pred p;\nsetp.ne.s32 p, %2, 0;\n@p st.global.u32 [%0], %1;\n}"
                         ::"l"(out + cta * 4 + lane * 2), "r"(pack_bf16(v0, v1)), "r"((int)(real && lane < 2)) : "memory");
            asm volatile("{\n.reg .pred p;\nsetp.ne.s32 p, %2, 0;\n@p st.global.u32 [%0], %1;\n}"
                         ::"l"(lane ? &g_s.prog : &g_s.epoch), "r"(lane ? 0u : tag), "r"((int)(real && lane < 2 && cta == 0)) : "memory");
        }
    }
}

}

extern "C" void kernel_launch(void* const* d_in, const int* in_sizes, int n_in, void* d_out, int out_size) {
    (void)in_sizes; (void)n_in; (void)out_size;
    static bool init = false;
    if (!init) {
        cudaFuncSetAttribute(fused_kernel, cudaFuncAttributeMaxDynamicSharedMemorySize, SM_TOTAL);
        init = true;
    }
    fused_kernel<<<NCTA, NTHREADS, SM_TOTAL>>>(
        (const __nv_bfloat16*)d_in[0], (const __nv_bfloat16*)d_in[1], (const __nv_bfloat16*)d_in[2],
        (const __nv_bfloat16*)d_in[3], (const __nv_bfloat16*)d_in[4], (const __nv_bfloat16*)d_in[6],
        (const __nv_bfloat16*)d_in[7], (const __nv_bfloat16*)d_in[8], (const __nv_bfloat16*)d_in[9],
        (__nv_bfloat16*)d_out);
}
```

```cpp
#include <cuda_runtime.h>
#include <cuda_bf16.h>
#include <stdint.h>

namespace {

constexpr int D_MODEL = 512;
constexpr int NH = 32;
constexpr int SK = 8192;
constexpr int DH = 128;
constexpr int FF = 1376;
constexpr int NSPLIT = 4;
constexpr int NCTA = NH * NSPLIT;
constexpr int KEYS_CTA = SK / NSPLIT;
constexpr int NW = 8;
constexpr int WT_BYTES = 32 * DH * 2;
constexpr int TW = 2;
constexpr int NS = 12;
constexpr int WIN = 4;
constexpr int FB = 160;
constexpr int FLAG_AT = 2;
constexpr int TT_BYTES = TW * WT_BYTES;
constexpr int SLOT_BYTES = TT_BYTES + 256;
constexpr int TPW = KEYS_CTA / 32 / NW;
constexpr int NTT = 2 * TPW * NW / TW;
constexpr int NTHREADS = NW * 32 + 64;

constexpr int SM_RING = 0;
constexpr int SM_RED = SM_RING + NS * SLOT_BYTES;
constexpr int RED_WSTRIDE = 2096;
constexpr int SM_SS = SM_RED;
constexpr int SM_P = SM_RED + NW * RED_WSTRIDE;
constexpr int SM_Q = SM_P + NW * TPW * 32 * 2;
constexpr int SM_O = SM_Q + 256;
constexpr int SM_GU = SM_O + 64;
constexpr int SM_MISC = SM_GU + 512;
constexpr int SM_BAR = SM_MISC + 128;
constexpr int SM_TOTAL = SM_BAR + 2 * NS * 8 + 512;
static_assert(SM_TOTAL <= 232448, "smem");

struct Scratch {
    uint2 x1[NCTA][256];
    uint2 x2[NCTA][128];
    uint4 x2ml[NCTA][2];
    uint4 x3[NCTA][NCTA][2];
    unsigned epoch;
    unsigned pad[31];
    unsigned prog;
};
__device__ Scratch g_s;

__device__ __forceinline__ uint32_t s2u(const void* p) { return (uint32_t)__cvta_generic_to_shared(p); }
__device__ __forceinline__ void mbar_init(uint32_t a, int c) {
    asm volatile("mbarrier.init.shared::cta.b64 [%0], %1;" ::"r"(a), "r"(c) : "memory");
}
__device__ __forceinline__ void mbar_expect(uint32_t a, uint32_t b) {
    asm volatile("mbarrier.arrive.expect_tx.shared::cta.b64 _, [%0], %1;" ::"r"(a), "r"(b) : "memory");
}
__device__ __forceinline__ void mbar_arrive(uint32_t a) {
    asm volatile("mbarrier.arrive.shared::cta.b64 _, [%0];" ::"r"(a) : "memory");
}
__device__ __forceinline__ void mbar_wait(uint32_t a, uint32_t ph) {
    uint32_t ok, n = 0;
    do {
        asm volatile("{\n.reg .pred p;\nmbarrier.try_wait.parity.shared::cta.b64 p, [%1], %2;\nselp.u32 %0, 1, 0, p;\n}"
                     : "=r"(ok) : "r"(a), "r"(ph) : "memory");
        if (++n > (1u << 22)) __trap();
    } while (!ok);
}
__device__ __forceinline__ uint32_t mbar_try(uint32_t a, uint32_t ph) {
    uint32_t ok;
    asm volatile("{\n.reg .pred p;\nmbarrier.try_wait.parity.shared::cta.b64 p, [%1], %2, 200;\nselp.u32 %0, 1, 0, p;\n}"
                 : "=r"(ok) : "r"(a), "r"(ph) : "memory");
    return ok;
}
__device__ __forceinline__ void mbar_wait_p(uint32_t a, uint32_t ph, int en) {
    uint32_t ok, n = 0;
    do {
        asm volatile("{\n.reg .pred p, q;\nsetp.eq.s32 p, %3, 0;\nsetp.ne.s32 q, %3, 0;\n@q mbarrier.try_wait.parity.shared::cta.b64 p, [%1], %2;\nselp.u32 %0, 1, 0, p;\n}"
                     : "=r"(ok) : "r"(a), "r"(ph), "r"(en) : "memory");
        if (++n > (1u << 22)) __trap();
    } while (!ok);
}
__device__ __forceinline__ void bulk_ld(uint32_t dst, const void* src, uint32_t bytes, uint32_t bar) {
    uint64_t pol;
    asm volatile("createpolicy.fractional.L2::evict_first.b64 %0, 1.0;" : "=l"(pol));
    asm volatile("cp.async.bulk.shared::cluster.global.mbarrier::complete_tx::bytes.L2::cache_hint [%0], [%1], %2, [%3], %4;"
                 ::"r"(dst), "l"(src), "r"(bytes), "r"(bar), "l"(pol) : "memory");
}
__device__ __forceinline__ uint4 ldg_nc(const void* p) {
    uint4 v;
    asm volatile("ld.global.nc.L1::no_allocate.v4.u32 {%0,%1,%2,%3}, [%4];"
                 : "=r"(v.x), "=r"(v.y), "=r"(v.z), "=r"(v.w) : "l"(p));
    return v;
}
__device__ __forceinline__ void ldg_nc_p(uint4& v, const void* a, int p) {
    uint64_t pol;
    asm volatile("createpolicy.fractional.L2::evict_first.b64 %0, 1.0;" : "=l"(pol));
    asm volatile("{\n.reg .pred p;\nsetp.ne.s32 p, %5, 0;\n@p ld.global.nc.L1::no_allocate.L2::cache_hint.v4.u32 {%0,%1,%2,%3}, [%4], %6;\n}"
                 : "+r"(v.x), "+r"(v.y), "+r"(v.z), "+r"(v.w) : "l"(a), "r"(p), "l"(pol));
}
__device__ __forceinline__ uint4 lds128(uint32_t a) {
    uint4 v;
    asm volatile("ld.shared.v4.u32 {%0,%1,%2,%3}, [%4];" : "=r"(v.x), "=r"(v.y), "=r"(v.z), "=r"(v.w) : "r"(a));
    return v;
}
__device__ __forceinline__ uint2 lds64(uint32_t a) {
    uint2 v;
    asm volatile("ld.shared.v2.u32 {%0,%1}, [%2];" : "=r"(v.x), "=r"(v.y) : "r"(a));
    return v;
}
__device__ __forceinline__ float lds32f(uint32_t a) {
    float v;
    asm volatile("ld.shared.f32 %0, [%1];" : "=f"(v) : "r"(a));
    return v;
}
__device__ __forceinline__ void sts128f_p(uint32_t a, const float (&c)[4], int p) {
    asm volatile("{\n.reg .pred p;\nsetp.ne.s32 p, %5, 0;\n@p st.shared.v4.f32 [%0], {%1,%2,%3,%4};\n}"
                 ::"r"(a), "f"(c[0]), "f"(c[1]), "f"(c[2]), "f"(c[3]), "r"(p) : "memory");
}
__device__ __forceinline__ void ld_ll2_p(uint2& v, const void* a, int p) {
    asm volatile("{\n.reg .pred p;\nsetp.ne.s32 p, %3, 0;\n@p ld.relaxed.gpu.global.v2.u32 {%0,%1}, [%2];\n}"
                 : "+r"(v.x), "+r"(v.y) : "l"(a), "r"(p) : "memory");
}
__device__ __forceinline__ void ld_ll4_p(uint4& v, const void* a, int p) {
    asm volatile("{\n.reg .pred p;\nsetp.ne.s32 p, %5, 0;\n@p ld.relaxed.gpu.global.v4.u32 {%0,%1,%2,%3}, [%4];\n}"
                 : "+r"(v.x), "+r"(v.y), "+r"(v.z), "+r"(v.w) : "l"(a), "r"(p) : "memory");
}
__device__ __forceinline__ void st_ll_p(uint2* a, float v, unsigned tag, int p) {
    asm volatile("{\n.reg .pred p;\nsetp.ne.s32 p, %3, 0;\n@p st.relaxed.gpu.global.v2.u32 [%0], {%1,%2};\n}"
                 ::"l"(a), "r"(__float_as_uint(v)), "r"(tag), "r"(p) : "memory");
}
__device__ __forceinline__ void st_ll4_p(void* a, float v0, float v1, unsigned tag, int p) {
    asm volatile("{\n.reg .pred p;\nsetp.ne.s32 p, %4, 0;\n@p st.relaxed.gpu.global.v4.u32 [%0], {%1,%2,%3,%2};\n}"
                 ::"l"(a), "r"(__float_as_uint(v0)), "r"(tag), "r"(__float_as_uint(v1)), "r"(p) : "memory");
}
__device__ __forceinline__ void mma16816(float (&c)[4], uint32_t a0, uint32_t a1, uint32_t a2, uint32_t a3,
                                         uint32_t b0, uint32_t b1) {
    asm volatile("mma.sync.aligned.m16n8k16.row.col.f32.bf16.bf16.f32 {%0,%1,%2,%3}, {%4,%5,%6,%7}, {%8,%9}, {%0,%1,%2,%3};"
                 : "+f"(c[0]), "+f"(c[1]), "+f"(c[2]), "+f"(c[3])
                 : "r"(a0), "r"(a1), "r"(a2), "r"(a3), "r"(b0), "r"(b1));
}
__device__ __forceinline__ void gemv_mma(float (&acc)[2][4], const uint4& L0, const uint4& L1, uint32_t b0, uint32_t b1) {
    mma16816(acc[0], L0.x, L0.y, L1.x, L1.y, b0, b1);
    mma16816(acc[1], L0.z, L0.w, L1.z, L1.w, b0, b1);
}
__device__ __forceinline__ float ex2(float x) {
    float y; asm("ex2.approx.ftz.f32 %0, %1;" : "=f"(y) : "f"(x)); return y;
}
__device__ __forceinline__ float bf16r(float x) { return __bfloat162float(__float2bfloat16_rn(x)); }
__device__ __forceinline__ uint32_t pack_bf16(float lo, float hi) {
    uint32_t r; asm("cvt.rn.bf16x2.f32 %0, %1, %2;" : "=r"(r) : "f"(hi), "f"(lo)); return r;
}
__device__ __forceinline__ void bar_sync(int id, int n) { asm volatile("bar.sync %0, %1;" ::"r"(id), "r"(n) : "memory"); }
template <int ID, int N>
__device__ __forceinline__ void bar_sync_p(int p) {
    asm volatile("{\n.reg .pred p;\nsetp.ne.s32 p, %0, 0;\n@p bar.sync %1, %2;\n}" ::"r"(p), "n"(ID), "n"(N) : "memory");
}
__device__ __forceinline__ int opaque(int v) { asm volatile("" : "+r"(v)); return v; }

constexpr unsigned SPIN_LIMIT = 1u << 24;

__device__ __forceinline__ float gather_x1(uint2 (&p)[4], int h, int idx, unsigned tag) {
    unsigned n = 0;
    bool ok;
    do {
        ok = true;
#pragma unroll
        for (int i = 0; i < 4; i++) ld_ll2_p(p[i], &g_s.x1[h * 4 + i][idx], p[i].y != tag);
#pragma unroll
        for (int i = 0; i < 4; i++) ok = ok && p[i].y == tag;
        if (!ok) __nanosleep(100);
        if (++n > SPIN_LIMIT) __trap();
    } while (!ok);
    return (__uint_as_float(p[0].x) + __uint_as_float(p[1].x)) + (__uint_as_float(p[2].x) + __uint_as_float(p[3].x));
}

__global__ void __launch_bounds__(NTHREADS, 1)
fused_kernel(const __nv_bfloat16* __restrict__ x, const __nv_bfloat16* __restrict__ kc,
             const __nv_bfloat16* __restrict__ vc, const __nv_bfloat16* __restrict__ wq,
             const __nv_bfloat16* __restrict__ wo, const __nv_bfloat16* __restrict__ wg,
             const __nv_bfloat16* __restrict__ wu, const __nv_bfloat16* __restrict__ wd,
             const __nv_bfloat16* __restrict__ gate_w, __nv_bfloat16* __restrict__ out) {
    extern __shared__ __align__(1024) unsigned char smem[];
    if (threadIdx.x == 0)
        asm volatile("cp.async.bulk.prefetch.L2.global [%0], %1;"
                     ::"l"(reinterpret_cast<const unsigned char*>(kc) + (size_t)blockIdx.x * (KEYS_CTA * DH * 2)), "n"(2 * TT_BYTES) : "memory");
    const uint32_t sb = s2u(smem);
    const int tid = threadIdx.x, lane = tid & 31;
    const int w = __shfl_sync(0xffffffffu, tid >> 5, 0);
    const int g = lane >> 2, t = lane & 3;
    const int cta = blockIdx.x, h = cta >> 2, s = cta & 3;
    float* misc = reinterpret_cast<float*>(smem + SM_MISC);
    const uint32_t fullb = sb + SM_BAR, emptyb = sb + SM_BAR + NS * 8;
    const int nch = h < 12 ? 6 : 5;
    const int ch0 = h < 12 ? 6 * h : 72 + 5 * (h - 12);

    const size_t kvoff = ((size_t)h * SK + (size_t)s * KEYS_CTA) * (DH * 2);
    if (__builtin_expect(tid == NW * 32, 1)) {
#pragma unroll
        for (int i = 0; i < WIN; i++) mbar_init(fullb + i * 8, 1);
        asm volatile("fence.mbarrier_init.release.cluster;" ::: "memory");
#pragma unroll
        for (int i = 0; i < WIN; i++) {
            mbar_expect(fullb + i * 8, TT_BYTES);
            bulk_ld(sb + SM_RING + i * SLOT_BYTES, reinterpret_cast<const unsigned char*>(kc) + kvoff + i * TT_BYTES, TT_BYTES, fullb + i * 8);
        }
    }
    const int r0 = 128 * s + 16 * w + 4 * t;
    uint4 fq[2][2][2] = {};
    uint2 xw = make_uint2(0, 0);
    uint2 px[4] = {};
    unsigned tag;
    {
        const __nv_bfloat16* p = wq + (size_t)r0 * (NH * DH) + h * DH + g * 8;
        const int con = w < NW;
#pragma unroll
        for (int grp = 0; grp < 2; grp++)
#pragma unroll
            for (int r = 0; r < 2; r++)
#pragma unroll
                for (int win = 0; win < 2; win++)
                    ldg_nc_p(fq[grp][win][r], p + (size_t)(2 * grp + r) * (NH * DH) + win * 64, con);
        asm volatile("{\n.reg .pred p;\nsetp.ne.s32 p, %3, 0;\n@p ld.global.nc.v2.u32 {%0,%1}, [%2];\n}"
                     : "+r"(xw.x), "+r"(xw.y) : "l"(x + r0), "r"(con));
        asm volatile("ld.relaxed.gpu.global.u32 %0, [%1];" : "=r"(tag) : "l"(&g_s.epoch) : "memory");
    }
    if (__builtin_expect(w == NW, 1)) {
        if (lane == 0) {
#pragma unroll
            for (int i = WIN; i < NS; i++) mbar_init(fullb + i * 8, 1);
#pragma unroll
            for (int i = 0; i < NS; i++) mbar_init(emptyb + i * 8, TW);
            *reinterpret_cast<volatile int*>(misc + 19) = WIN;
            *reinterpret_cast<volatile int*>(misc + 20) = 0;
            asm volatile("fence.mbarrier_init.release.cluster;" ::: "memory");
        }
        __syncwarp();
        asm volatile("bar.arrive 3, %0;" ::"n"(NW * 32 + 32) : "memory");
        const unsigned char* src = reinterpret_cast<const unsigned char*>(kc) + kvoff + WIN * TT_BYTES;
        int slot = WIN, lslot = 0, landed = 0;
        uint32_t eph = 1, lph = 0, spins = 0;
#pragma unroll 1
        for (int j = WIN; j < NTT + 3; j++) {
            if (j == NTT / 2) src = reinterpret_cast<const unsigned char*>(vc) + kvoff;
            mbar_wait(emptyb + slot * 8, eph);
            while (landed < min(NTT, (j < NTT ? j : NTT) + 1 - *reinterpret_cast<volatile int*>(misc + 19))) {
                if (!mbar_try(fullb + lslot * 8, lph)) { if (++spins > (1u << 24)) __trap(); continue; }
                landed++;
                if (lane == 0) {
                    asm volatile("red.relaxed.gpu.global.add.u32 [%0], 1;" ::"l"(&g_s.prog) : "memory");
                    *reinterpret_cast<volatile int*>(misc + 20) = landed;
                }
                if (++lslot == NS) { lslot = 0; lph ^= 1; }
            }
            int n = 1, bytes = TT_BYTES;
            if (j >= NTT) {
                n = (j > NTT || s + 4 >= nch) ? 4 : 8;
                bytes = j > NTT ? 4096 : 2048;
                src = j > NTT ? reinterpret_cast<const unsigned char*>(wo + (size_t)(h * DH + 32 * s + (j - NTT - 1) * 16) * D_MODEL)
                              : reinterpret_cast<const unsigned char*>(wd + (size_t)(8 * (ch0 + s)) * D_MODEL);
            }
            if (lane == 0) {
                uint32_t dst = sb + SM_RING + slot * SLOT_BYTES;
                const uint32_t bar = fullb + slot * 8;
                mbar_expect(bar, n * bytes);
#pragma unroll 1
                for (int i = 0; i < n; i++) {
                    bulk_ld(dst, src + i * bytes + (i >= 4 ? 24576 : 0), bytes, bar);
                    dst += bytes + 32;
                }
                if (j == NTT - FLAG_AT) *reinterpret_cast<volatile int*>(misc + 18) = 1;
            }
            __syncwarp();
            src += TT_BYTES;
            if (++slot == NS) { slot = 0; eph ^= 1; }
        }
    }
    if (opaque(w) == NW) return;

    const uint32_t selR0 = (g & 1) ? 0x1044u : 0x4410u;
    const uint32_t selR1 = (g & 1) ? 0x3244u : 0x4432u;

    float acc[2][2][4] = {};
    float m = 0.f;

    if (__builtin_expect(w < NW, 1)) {
        uint4 fg[2][2][2] = {};
        st_ll_p(&g_s.x1[cta][tid], 0.f, 0, 1);
        uint32_t bx[2][2];
        {
            float aq[2][2][4] = {};
#pragma unroll
            for (int grp = 0; grp < 2; grp++) {
                const uint32_t c = grp ? xw.y : xw.x;
                bx[grp][0] = __byte_perm(c, 0, selR0); bx[grp][1] = __byte_perm(c, 0, selR1);
#pragma unroll
                for (int win = 0; win < 2; win++) gemv_mma(aq[win], fq[grp][win][0], fq[grp][win][1], bx[grp][0], bx[grp][1]);
            }
            const uint32_t a = sb + SM_RED + w * RED_WSTRIDE + g * 32 + (t >> 1) * 256 + (t & 1) * 16;
            float v[4];
#pragma unroll
            for (int e = 0; e < 4; e++) v[e] = (t & 2) ? ((t & 1) ? aq[1][1][e] : aq[1][0][e]) : ((t & 1) ? aq[0][1][e] : aq[0][0][e]);
            sts128f_p(a, v, 1);
        }
        {
            const size_t off = (size_t)r0 * FF + (ch0 + g) * 8;
            const int ok = g < nch;
#pragma unroll
            for (int grp = 0; grp < 2; grp++)
#pragma unroll
                for (int r = 0; r < 2; r++) {
                    ldg_nc_p(fg[grp][0][r], wg + off + (size_t)(2 * grp + r) * FF, ok);
                    ldg_nc_p(fg[grp][1][r], wu + off + (size_t)(2 * grp + r) * FF, ok);
                }
        }
        tag += 1;
        bar_sync(1, NW * 32);
        if (tid < 128) {
            float v = 0.f;
#pragma unroll
            for (int i = 0; i < NW; i++) v += lds32f(sb + SM_RED + i * RED_WSTRIDE + tid * 4);
            st_ll_p(&g_s.x1[cta][tid], v, tag, 1);
            v = gather_x1(px, h, tid, tag);
            reinterpret_cast<__nv_bfloat16*>(smem + SM_Q)[tid] = __float2bfloat16_rn(v);
        }
        bar_sync(3, NW * 32 + 32);
        if (tid == 0) *reinterpret_cast<volatile int*>(misc + 19) = WIN;
        st_ll_p(&g_s.x2[cta][tid >> 1], 0.f, 0, !(tid & 1));
        st_ll4_p(&g_s.x2ml[cta][tid & 1], 0.f, 0.f, 0, tid < 2);
        st_ll4_p(&g_s.x3[16 * w + 2 * g + (t >> 1)][cta][t & 1], 0.f, 0.f, 0, 1);

        uint4 qf[4];
#pragma unroll
        for (int c = 0; c < 4; c++) qf[c] = lds128(sb + SM_Q + (t + 4 * (c ^ (g & 1))) * 16);
        float mx = -INFINITY;
        float* ss = reinterpret_cast<float*>(smem + SM_SS + w * RED_WSTRIDE + 1024) + lane;
        int slot = w / TW;
        uint32_t ph = 0;
        const uint32_t ring = sb + SM_RING + (w % TW) * WT_BYTES;
#pragma unroll 1
        for (int i = 0; i < TPW; i++) {
            mbar_wait(fullb + slot * 8, ph);
            const uint32_t tb = ring + slot * SLOT_BYTES + g * 256;
            float c0[4] = {}, c1[4] = {};
#pragma unroll
            for (int c = 0; c < 4; c++) {
                const uint32_t a = tb + (t + 4 * (c ^ (g & 1))) * 16;
                const uint4 A0 = lds128(a), A1 = lds128(a + 8 * 256), A2 = lds128(a + 16 * 256), A3 = lds128(a + 24 * 256);
                mma16816(c0, A0.x, A1.x, A0.y, A1.y, qf[c].x, qf[c].y);
                mma16816(c1, A2.x, A3.x, A2.y, A3.y, qf[c].x, qf[c].y);
                mma16816(c0, A0.z, A1.z, A0.w, A1.w, qf[c].z, qf[c].w);
                mma16816(c1, A2.z, A3.z, A2.w, A3.w, qf[c].z, qf[c].w);
            }
            __syncwarp();
            if (lane == 0) mbar_arrive(emptyb + slot * 8);
            const float e0 = (g & 1) ? c0[1] : c0[0], e1 = (g & 1) ? c0[3] : c0[2];
            const float e2 = (g & 1) ? c1[1] : c1[0], e3 = (g & 1) ? c1[3] : c1[2];
            const float sc = bf16r(bf16r((t & 2) ? ((t & 1) ? e3 : e2) : ((t & 1) ? e1 : e0)) * 0.08838834764831845f) * 1.4426950408889634f;
            ss[i * 32] = sc;
            mx = fmaxf(mx, sc);
            slot += NW / TW;
            if (slot >= NS) { slot -= NS; ph ^= 1; }
        }
#pragma unroll
        for (int o = 16; o; o >>= 1) mx = fmaxf(mx, __shfl_xor_sync(0xffffffffu, mx, o));
        if (lane == 0) misc[w] = mx;
        {
            float ag[2][2][4] = {};
#pragma unroll
            for (int grp = 0; grp < 2; grp++)
#pragma unroll
                for (int mm = 0; mm < 2; mm++) gemv_mma(ag[mm], fg[grp][mm][0], fg[grp][mm][1], bx[grp][0], bx[grp][1]);
            const uint32_t a = sb + SM_RED + w * RED_WSTRIDE + 512 + g * 32 + (t >> 1) * 256 + (t & 1) * 16;
            float v[4];
#pragma unroll
            for (int e = 0; e < 4; e++) v[e] = (t & 2) ? ((t & 1) ? ag[1][1][e] : ag[1][0][e]) : ((t & 1) ? ag[0][1][e] : ag[0][0][e]);
            sts128f_p(a, v, 1);
        }
        bar_sync(1, NW * 32);
        if (tid >= 128) {
            float v = 0.f;
#pragma unroll
            for (int i = 0; i < NW; i++) v += lds32f(sb + SM_RED + i * RED_WSTRIDE + tid * 4);
            st_ll_p(&g_s.x1[cta][tid], v, tag, 1);
        }
        {
            const float4 a = *reinterpret_cast<const float4*>(misc), b = *reinterpret_cast<const float4*>(misc + 4);
            m = fmaxf(fmaxf(fmaxf(a.x, a.y), fmaxf(a.z, a.w)), fmaxf(fmaxf(b.x, b.y), fmaxf(b.z, b.w)));
            __nv_bfloat16* pp = reinterpret_cast<__nv_bfloat16*>(smem + SM_P) + w * (TPW * 32) + 8 * t + g;
            float l = 0.f;
#pragma unroll
            for (int i = 0; i < TPW; i++) {
                const __nv_bfloat16 p = __float2bfloat16_rn(ex2(ss[i * 32] - m));
                pp[i * 32] = p;
                l += __bfloat162float(p);
            }
#pragma unroll
            for (int o = 16; o; o >>= 1) l += __shfl_xor_sync(0xffffffffu, l, o);
            if (lane == 0) misc[8 + w] = l;
            __syncwarp();
        }

        const bool actP = (g >> 1) == t;
        const uint32_t selP0 = actP ? selR0 : 0x4444u;
        const uint32_t selP1 = actP ? selR1 : 0x4444u;
        const uint32_t voff = (8 * t) * 256 + ((g + 2 * t) & 7) * 16;
#pragma unroll 1
        for (int i = 0; i < TPW; i++) {
            if (i == TPW / 2 && w >= 4) reinterpret_cast<float*>(smem + SM_GU)[tid - 128] = bf16r(gather_x1(px, h, tid, tag));
            const uint4 pf = lds128(sb + SM_P + (w * (TPW * 32) + i * 32 + 8 * t) * 2);
            mbar_wait(fullb + slot * 8, ph);
            const uint32_t tb = ring + slot * SLOT_BYTES + voff;
            const uint32_t pw[4] = {pf.x, pf.y, pf.z, pf.w};
#pragma unroll
            for (int grp = 0; grp < 4; grp++) {
                const uint32_t b0 = __byte_perm(pw[grp], 0, selP0), b1 = __byte_perm(pw[grp], 0, selP1);
                const uint32_t a = tb + grp * 512;
                const uint4 A0 = lds128(a), A1 = lds128(a + 256), A2 = lds128(a + 128), A3 = lds128(a + 256 + 128);
                gemv_mma(acc[0], A0, A1, b0, b1);
                gemv_mma(acc[1], A2, A3, b0, b1);
            }
            __syncwarp();
            if (lane == 0) mbar_arrive(emptyb + slot * 8);
            slot += NW / TW;
            if (slot >= NS) { slot -= NS; ph ^= 1; }
        }
    } else {
        if (lane == 0) *reinterpret_cast<volatile int*>(misc + 18) = 0;
        tag += 1;
        uint4 xa = ldg_nc(x + lane * 16), xb = ldg_nc(x + lane * 16 + 8);
        uint4 ga = ldg_nc(gate_w + lane * 16), gb = ldg_nc(gate_w + lane * 16 + 8);
        const uint32_t xr[8] = {xa.x, xa.y, xa.z, xa.w, xb.x, xb.y, xb.z, xb.w};
        const uint32_t gr[8] = {ga.x, ga.y, ga.z, ga.w, gb.x, gb.y, gb.z, gb.w};
        float a = 0.f;
#pragma unroll
        for (int i = 0; i < 8; i++) {
            a += bf16r(__uint_as_float(xr[i] << 16) * __uint_as_float(gr[i] << 16));
            a += bf16r(__uint_as_float(xr[i] & 0xffff0000u) * __uint_as_float(gr[i] & 0xffff0000u));
        }
#pragma unroll
        for (int o = 16; o; o >>= 1) a += __shfl_xor_sync(0xffffffffu, a, o);
        a = bf16r(a);
        const float gate = bf16r(1.f / (1.f + __expf(-a)));
        if (lane == 0) {
            misc[16] = gate;
            misc[17] = bf16r(1.f - gate);
        }
    }

    const int is_aux = opaque(w > NW);
    const int col = tid >> 1, half = tid & 1;
#pragma unroll 1
    for (int pass = is_aux ? 0 : 1; pass < 2; pass++) {
        const int real = opaque(pass);
        const int con = opaque(!is_aux);
        float af[2][4] = {};
        uint4 fo[4][2] = {};
        if (con || !real) {
            const uint32_t a = sb + SM_RED + w * RED_WSTRIDE + t * 512 + (t >> 1) * 16 + ((g + 2 * t) & 7) * 32;
            sts128f_p(a, acc[0][0], con); sts128f_p(a + 16, acc[0][1], con);
            sts128f_p(a + 256, acc[1][0], con); sts128f_p(a + 256 + 16, acc[1][1], con);
            bar_sync_p<1, NW * 32>(con);
            float v = 0.f;
            const uint32_t rp = sb + SM_RED + half * (4 * RED_WSTRIDE) + col * 4;
            float vv[4];
#pragma unroll
            for (int i = 0; i < 4; i++)
                vv[i] = (lds32f(rp + i * RED_WSTRIDE) + lds32f(rp + i * RED_WSTRIDE + 512)) +
                        (lds32f(rp + i * RED_WSTRIDE + 1024 + 16) + lds32f(rp + i * RED_WSTRIDE + 1536 + 16));
            v = (vv[0] + vv[1]) + (vv[2] + vv[3]);
            v += __shfl_xor_sync(0xffffffffu, v, 1);
            st_ll_p(&g_s.x2[cta][col], v, tag, con && half == 0);
            {
                const uint4 la = lds128(sb + SM_MISC + 32), lb = lds128(sb + SM_MISC + 48);
                const float l = ((__uint_as_float(la.x) + __uint_as_float(la.y)) + (__uint_as_float(la.z) + __uint_as_float(la.w))) +
                                ((__uint_as_float(lb.x) + __uint_as_float(lb.y)) + (__uint_as_float(lb.z) + __uint_as_float(lb.w)));
                st_ll4_p(&g_s.x2ml[cta][tid & 1], m, l, tag, tid < 2);
            }
            uint32_t hfrag[2];
#pragma unroll
            for (int ci = 0; ci < 2; ci++) {
                const int f = 8 * (s + 4 * ci) + 2 * t;
                const uint2 gg = lds64(sb + SM_GU + f * 4), uu = lds64(sb + SM_GU + 256 + f * 4);
                hfrag[ci] = pack_bf16(__uint_as_float(gg.x) * __uint_as_float(uu.x), __uint_as_float(gg.y) * __uint_as_float(uu.y));
            }
            const uint32_t wa = sb + SM_RING + (w & 7) * 128 + g * 16;
            mbar_wait_p(fullb + (NTT % NS) * 8, (NTT / NS) & 1, con);
            {
                const uint32_t a0 = wa + (NTT % NS) * SLOT_BYTES + t * 2080;
                uint32_t b0 = __byte_perm(hfrag[0], 0, selR0), b1 = __byte_perm(hfrag[0], 0, selR1);
                gemv_mma(af, lds128(a0), lds128(a0 + 1024), b0, b1);
                if (s + 4 < nch) {
                    b0 = __byte_perm(hfrag[1], 0, selR0), b1 = __byte_perm(hfrag[1], 0, selR1);
                    gemv_mma(af, lds128(a0 + 4 * 2080), lds128(a0 + 4 * 2080 + 1024), b0, b1);
                }
            }
#pragma unroll
            for (int k = 0; k < 2; k++) {
                mbar_wait_p(fullb + ((NTT + 1 + k) % NS) * 8, ((NTT + 1 + k) / NS) & 1, con);
                const uint32_t a0 = wa + ((NTT + 1 + k) % NS) * SLOT_BYTES + t * 4128;
                fo[2 * k][0] = lds128(a0);
                fo[2 * k][1] = lds128(a0 + 1024);
                fo[2 * k + 1][0] = lds128(a0 + 2048);
                fo[2 * k + 1][1] = lds128(a0 + 3072);
            }
        }
        uint4 e[8];
        const uint4* src3 = &g_s.x3[cta][lane >> 1][lane & 1];
        if (is_aux) {
            uint2 o4[4];
            uint4 ml[4];
            const uint2* src = &g_s.x2[h * 4][32 * s + lane];
            unsigned n = 0;
            bool ok;
            if (real) {
                while (*reinterpret_cast<volatile int*>(misc + 18) == 0) {
                    {
                        const int own0 = *reinterpret_cast<volatile int*>(misc + 20);
                        unsigned G;
                        asm volatile("ld.relaxed.gpu.global.u32 %0, [%1];" : "=r"(G) : "l"(&g_s.prog) : "memory");
                        const int own1 = *reinterpret_cast<volatile int*>(misc + 20);
                        const int lead = (own0 + own1) * (NCTA / 2) - (int)G;
                        const int win = WIN + (lead > 2 * FB ? -2 : lead > FB ? -1 : lead < -2 * FB ? 2 : lead < -FB ? 1 : 0);
                        if (lane == 0 && own1 >= 8) *reinterpret_cast<volatile int*>(misc + 19) = win;
                    }
                    __nanosleep(200);
                    if (++n > SPIN_LIMIT) __trap();
                }
            }
#pragma unroll
            for (int k = 0; k < 8; k++) {
                e[k] = make_uint4(0, tag, 0, tag);
                ld_ll4_p(e[k], src3 + k * 32, real);
            }
            do {
                ok = true;
#pragma unroll
                for (int i = 0; i < 4; i++) {
                    o4[i] = make_uint2(0, tag);
                    ml[i] = make_uint4(0, tag, 0, tag);
                    ld_ll2_p(o4[i], src + i * 128, real);
                    ld_ll4_p(ml[i], &g_s.x2ml[h * 4 + i][0], real);
                }
#pragma unroll
                for (int i = 0; i < 4; i++) ok = ok && o4[i].y == tag && ml[i].y == tag && ml[i].w == tag;
                if (++n > SPIN_LIMIT) __trap();
            } while (!ok);
            const float M = fmaxf(fmaxf(__uint_as_float(ml[0].x), __uint_as_float(ml[1].x)),
                                  fmaxf(__uint_as_float(ml[2].x), __uint_as_float(ml[3].x)));
            float den = 0.f, num = 0.f;
#pragma unroll
            for (int i = 0; i < 4; i++) {
                const float wt = ex2(__uint_as_float(ml[i].x) - M);
                den += wt * __uint_as_float(ml[i].z);
                num += wt * __uint_as_float(o4[i].x);
            }
            const uint32_t p0 = pack_bf16(__fdividef(num, den), 0.f);
            asm volatile("{\n.reg .pred p;\nsetp.ne.s32 p, %2, 0;\n@p st.shared.u16 [%0], %1;\n}"
                         ::"r"(sb + SM_O + (((lane >> 2) & 3) * 8 + (lane >> 4) * 4 + (lane & 3)) * 2), "h"((unsigned short)p0), "r"(real) : "memory");
        }
        bar_sync_p<2, NW * 32 + 32>(real);
        if (con || !real) {
            const uint4 ow = lds128(sb + SM_O + t * 16);
            const uint2 gt = lds64(sb + SM_MISC + 64);
            const uint32_t oc[4] = {ow.x, ow.y, ow.z, ow.w};
            float a0[2][4] = {}, a1[2][4] = {};
            float a2[2][4] = {}, a3[2][4] = {};
            gemv_mma(a0, fo[0][0], fo[0][1], __byte_perm(oc[0], 0, selR0), __byte_perm(oc[0], 0, selR1));
            gemv_mma(a1, fo[1][0], fo[1][1], __byte_perm(oc[1], 0, selR0), __byte_perm(oc[1], 0, selR1));
            gemv_mma(a2, fo[2][0], fo[2][1], __byte_perm(oc[2], 0, selR0), __byte_perm(oc[2], 0, selR1));
            gemv_mma(a3, fo[3][0], fo[3][1], __byte_perm(oc[3], 0, selR0), __byte_perm(oc[3], 0, selR1));
#pragma unroll
            for (int j = 0; j < 2; j++)
#pragma unroll
                for (int q = 0; q < 4; q++) { a0[j][q] += a2[j][q]; a1[j][q] += a3[j][q]; }
            const float gate = __uint_as_float(gt.x), omg = __uint_as_float(gt.y);
            float r[2][4];
#pragma unroll
            for (int j = 0; j < 2; j++)
#pragma unroll
                for (int q = 0; q < 4; q++) r[j][q] = gate * (a0[j][q] + a1[j][q]) + omg * af[j][q];
            const float v0 = (t & 2) ? ((t & 1) ? r[1][2] : r[1][0]) : ((t & 1) ? r[0][2] : r[0][0]);
            const float v1 = (t & 2) ? ((t & 1) ? r[1][3] : r[1][1]) : ((t & 1) ? r[0][3] : r[0][1]);
            st_ll4_p(&g_s.x3[(16 * w + 2 * g + (t >> 1)) & (NCTA - 1)][cta][t & 1], v0, v1, tag, con);
        }
        if (is_aux) {
            unsigned n = 0;
            bool ok;
            do {
                ok = true;
#pragma unroll
                for (int k = 0; k < 8; k++) ld_ll4_p(e[k], src3 + k * 32, e[k].y != tag || e[k].w != tag);
#pragma unroll
                for (int k = 0; k < 8; k++) ok = ok && e[k].y == tag && e[k].w == tag;
                if (++n > SPIN_LIMIT) __trap();
            } while (!ok);
            float v0 = 0.f, v1 = 0.f;
#pragma unroll
            for (int k = 0; k < 8; k++) { v0 += __uint_as_float(e[k].x); v1 += __uint_as_float(e[k].z); }
            __syncwarp();
#pragma unroll
            for (int o = 16; o > 1; o >>= 1) {
                v0 += __shfl_xor_sync(0xffffffffu, v0, o);
                v1 += __shfl_xor_sync(0xffffffffu, v1, o);
            }
            asm volatile("{\n.reg .pred p;\nsetp.ne.s32 p, %2, 0;\n@p st.global.u32 [%0], %1;\n}"
                         ::"l"(out + cta * 4 + lane * 2), "r"(pack_bf16(v0, v1)), "r"((int)(real && lane < 2)) : "memory");
            asm volatile("{\n.reg .pred p;\nsetp.ne.s32 p, %2, 0;\n@p st.global.u32 [%0], %1;\n}"
                         ::"l"(lane ? &g_s.prog : &g_s.epoch), "r"(lane ? 0u : tag), "r"((int)(real && lane < 2 && cta == 0)) : "memory");
        }
    }
}

}

extern "C" void kernel_launch(void* const* d_in, const int* in_sizes, int n_in, void* d_out, int out_size) {
    (void)in_sizes; (void)n_in; (void)out_size;
    static bool init = false;
    if (!init) {
        cudaFuncSetAttribute(fused_kernel, cudaFuncAttributeMaxDynamicSharedMemorySize, SM_TOTAL);
        init = true;
    }
    fused_kernel<<<NCTA, NTHREADS, SM_TOTAL>>>(
        (const __nv_bfloat16*)d_in[0], (const __nv_bfloat16*)d_in[1], (const __nv_bfloat16*)d_in[2],
        (const __nv_bfloat16*)d_in[3], (const __nv_bfloat16*)d_in[4], (const __nv_bfloat16*)d_in[6],
        (const __nv_bfloat16*)d_in[7], (const __nv_bfloat16*)d_in[8], (const __nv_bfloat16*)d_in[9],
        (__nv_bfloat16*)d_out);
}
```
